```python
import torch

def _softmax(x, axis=-1):
    return torch.softmax(x, dim=axis)

def _gelu(x):
    return torch.nn.functional.gelu(x, approximate='tanh')

def _silu(x):
    return torch.nn.functional.silu(x)

def _sigmoid(x):
    return torch.sigmoid(x)

def _layernorm(x, axis=-1, eps=1e-05):
    m = x.mean(dim=axis, keepdim=True)
    v = x.var(dim=axis, keepdim=True, unbiased=False)
    return (x - m) / torch.sqrt(v + eps)

def _scatter_add(tgt, idx, src, axis=0):
    return tgt.clone().index_add_(axis, idx, src)

def _segment_sum(src, seg, n):
    out = torch.zeros((n,) + src.shape[1:], dtype=src.dtype)
    return out.index_add_(0, seg, src)

def _pad(x, pw):
    flat = tuple((v for pair in reversed(pw) for v in pair))
    return torch.nn.functional.pad(x, flat)
kernel_name = 'concat_heads__sliding_local_dilated__memory_aug_recurrent_mem_tr__prompt'

def setup_inputs():

    _w = lambda a: (lambda t: t.to(torch.bfloat16) if t.is_floating_point() else t)(torch.as_tensor(a))

    def _A_setup():
        B, S, D = (1, 2048, 640)
        return {'x': _w((lambda *s: torch.randn(*s, dtype=torch.bfloat16) * 0.2)(B, S, D)), 'wqkv': _w((lambda *s: torch.randn(*s, dtype=torch.bfloat16) * 0.2)(D, 3 * D)), 'wo': _w((lambda *s: torch.randn(*s, dtype=torch.bfloat16) * 0.05)(D, D))}
    _A_in = _A_setup()

    def _B_setup():
        B, S, Dm = (1, 2048, 640)
        H, Dh = (32, 192)
        M, seg = (8, 32)
        seg = min(seg, S)
        S = S // seg * seg
        return {'x': _w((lambda *s: torch.randn(*s, dtype=torch.bfloat16) * 0.05)(B, S, Dm)), 'mem0': _w((lambda *s: torch.randn(*s, dtype=torch.bfloat16) * 1.6)(B, M, Dm)), 'Wq': _w((lambda *s: torch.randn(*s, dtype=torch.bfloat16) * 0.8)(Dm, H, Dh) * Dm ** (-0.5)), 'Wk': _w((lambda *s: torch.randn(*s, dtype=torch.bfloat16) * 0.8)(Dm, H, Dh) * Dm ** (-0.5)), 'Wv': _w((lambda *s: torch.randn(*s, dtype=torch.bfloat16) * 1.6)(Dm, H, Dh) * Dm ** (-0.5)), 'Wo': _w((lambda *s: torch.randn(*s, dtype=torch.bfloat16) * 1.6)(H, Dh, Dm) * (H * Dh) ** (-0.5)), 'seg_len': seg}
    _B_in = _B_setup()
    return {'A_x': _A_in['x'], 'A_wqkv': _A_in['wqkv'], 'A_wo': _A_in['wo'], 'B_x': _B_in['x'], 'B_mem0': _B_in['mem0'], 'B_Wq': _B_in['Wq'], 'B_Wk': _B_in['Wk'], 'B_Wv': _B_in['Wv'], 'B_Wo': _B_in['Wo'], 'B_seg_len': _B_in['seg_len']}

def reference(A_x, A_wqkv, A_wo, B_x, B_mem0, B_Wq, B_Wk, B_Wv, B_Wo, B_seg_len):

    def _A_ref(x, wqkv, wo):
        B, S, D = x.shape
        H = 32
        Dh = D // H
        W, dil = (8, 2)
        qkv = (lambda x, *d: x.permute(*d))((x @ wqkv).reshape(B, S, 3, H, Dh), 2, 0, 3, 1, 4)
        q, k, v = (qkv[0], qkv[1], qkv[2])
        scale = Dh ** (-0.5)
        pos = torch.arange(S)
        off = torch.arange(W) * dil
        idx = pos[:, None] - off[None, :]
        mask = idx >= 0
        idx_c = torch.where(mask, idx, 0).reshape(-1)
        kg = k[:, :, idx_c, :].reshape(B, H, S, W, Dh)
        vg = v[:, :, idx_c, :].reshape(B, H, S, W, Dh)
        logits = torch.einsum('bhsd,bhswd->bhsw', q, kg) * scale
        logits = torch.where(mask[None, None, :, :], logits, -1000000000.0)
        attn = _softmax(logits, axis=-1)
        o = torch.einsum('bhsw,bhswd->bhsd', attn, vg)
        return (lambda x, *d: x.permute(*d))(o, 0, 2, 1, 3).reshape(B, S, D) @ wo

    def _B_ref(x, mem0, Wq, Wk, Wv, Wo, seg_len):
        B, S, Dm = x.shape
        H, Dh = (Wq.shape[1], Wq.shape[2])
        M = mem0.shape[1]
        scale = Dh ** (-0.5)
        n_seg = S // seg_len
        L = M + seg_len
        idx = torch.arange(L)
        mask = (idx[:, None] < M) | (idx[:, None] >= idx[None, :])
        mem = mem0
        outs = []
        for s in range(n_seg):
            xs = x[:, s * seg_len:(s + 1) * seg_len, :].clone()
            h = torch.concatenate([mem, xs], axis=1)
            q = torch.einsum('btd,dhe->bhte', h, Wq)
            k = torch.einsum('btd,dhe->bhte', h, Wk)
            v = torch.einsum('btd,dhe->bhte', h, Wv)
            scores = torch.einsum('bhqe,bhke->bhqk', q, k) * scale
            scores = torch.where(mask[None, None], scores, -1000000000.0)
            p = _softmax(scores, axis=-1)
            o = torch.einsum('bhqk,bhke->bhqe', p, v)
            o = torch.einsum('bhte,hed->btd', o, Wo)
            mem = o[:, :M, :].clone()
            outs.append(o[:, M:, :])
        return torch.concatenate(outs, axis=1)
    a = _A_ref(A_x, A_wqkv, A_wo)
    b = _B_ref(B_x, B_mem0, B_Wq, B_Wk, B_Wv, B_Wo, B_seg_len)
    return torch.concatenate([a, b], axis=-1)
```

```cpp
#include <cuda_runtime.h>
#include <cuda_bf16.h>
#include <cuda.h>
#include <stdint.h>
#include <string.h>
#include <type_traits>

typedef __nv_bfloat16 bf16;

constexpr int SEQ = 2048, DM = 640, NH = 32, DH = 192, HE = NH * DH;
constexpr int NSEG = 64;
constexpr int OUTW = 1280;

__device__ uint4 g_xch[(4 << 20) / 16];
__device__ uint4 g_near4[96 * 2];
__device__ bf16  g_ox[SEQ * HE];
__device__ bf16  g_qkvA[SEQ * 3 * DM];
__device__ bf16  g_oA[SEQ * DM];
__device__ uint4 g_vx[96 * NSEG * 256];
__device__ uint4 g_op[NSEG * 70 * 256];
__device__ uint4 g_tail[4 * 32 * 80 * 32];
__device__ uint32_t g_epoch;
__device__ uint32_t g_flagv[96 * 64];
__device__ uint32_t g_prog[96];
__device__ uint32_t g_cnt[256];
constexpr int CNT_Q = 0, CNT_ATT = 8, CNT_O = 16, SPIN_LIM = 1 << 15;
#ifdef TL
__device__ uint32_t g_tl[132 * 80];
__device__ uint32_t g_tc[132 * 80];
#define TLS(row, i) do { uint32_t t_, c_; asm volatile("mov.u32 %0, %%globaltimer_lo; mov.u32 %1, %%clock;" : "=r"(t_), "=r"(c_)); g_tl[(row) * 80 + (i)] = t_; g_tc[(row) * 80 + (i)] = c_; } while (0)
#define TLC(w, i) do { if (warp == (w)) asm volatile("{.reg .b32 t; mov.u32 t, %%globaltimer_lo; st.shared.b32 [%0], t; mov.u32 t, %%clock; st.shared.b32 [%0 + 4], t;}" :: "r"(sb + OFF_DBG + (i) * 8) : "memory"); } while (0)
#else
#define TLS(row, i) do { } while (0)
#define TLC(w, i) do { } while (0)
#endif
#ifdef DEV
__device__ uint32_t g_dbg[96 * 512];
__device__ uint32_t g_cal[96 * 8];
#endif

__device__ __forceinline__ uint32_t smem_u32(const void* p) { return (uint32_t)__cvta_generic_to_shared(p); }
__device__ __forceinline__ uint32_t pack2(float lo, float hi) {
    uint32_t r; asm("cvt.rn.bf16x2.f32 %0, %1, %2;" : "=r"(r) : "f"(hi), "f"(lo)); return r;
}
__device__ __forceinline__ float ex2(float x) { float r; asm("ex2.approx.ftz.f32 %0, %1;" : "=f"(r) : "f"(x)); return r; }
__device__ __forceinline__ float rcpf(float x) { float r; asm("rcp.approx.ftz.f32 %0, %1;" : "=f"(r) : "f"(x)); return r; }
__device__ __forceinline__ void mbar_init(uint32_t bar, uint32_t cnt) {
    asm volatile("mbarrier.init.shared::cta.b64 [%0], %1;" :: "r"(bar), "r"(cnt) : "memory");
}
__device__ __forceinline__ void mbar_arrive(uint32_t bar) {
    asm volatile("mbarrier.arrive.shared::cta.b64 _, [%0];" :: "r"(bar) : "memory");
}
__device__ __forceinline__ void mbar_expect(uint32_t bar, uint32_t bytes) {
    asm volatile("mbarrier.arrive.expect_tx.shared::cta.b64 _, [%0], %1;" :: "r"(bar), "r"(bytes) : "memory");
}
constexpr int WAIT_LIM = 2048;
__device__ __forceinline__ void mbar_wait(uint32_t bar, uint32_t parity) {
    asm volatile("{.reg .pred p, q; .reg .u32 c; mov.u32 c, 512;\n"
                 "WL_%=: mbarrier.try_wait.parity.shared::cta.b64 p, [%0], %1;\n"
                 "@p bra WD_%=; sub.u32 c, c, 1; setp.ne.u32 q, c, 0; @q bra WL_%=;\n"
                 "WD_%=: }" :: "r"(bar), "r"(parity) : "memory");
}
__device__ __forceinline__ void mbar_wait_long(uint32_t bar, uint32_t parity) {
    asm volatile("{.reg .pred p, q; .reg .u32 c; mov.u32 c, 16384;\n"
                 "WL_%=: mbarrier.try_wait.parity.shared::cta.b64 p, [%0], %1;\n"
                 "@p bra WD_%=; sub.u32 c, c, 1; setp.ne.u32 q, c, 0; @q bra WL_%=;\n"
                 "WD_%=: }" :: "r"(bar), "r"(parity) : "memory");
}
__device__ __forceinline__ void bar_sync(int id, int n) { asm volatile("bar.sync %0, %1;" :: "r"(id), "r"(n) : "memory"); }
__device__ __forceinline__ void bar_arrive(int id, int n) { asm volatile("bar.arrive %0, %1;" :: "r"(id), "r"(n) : "memory"); }
__device__ __forceinline__ void tma2d(uint32_t dst, const CUtensorMap* tm, int c0, int c1, uint32_t bar) {
    asm volatile("cp.async.bulk.tensor.2d.shared::cluster.global.mbarrier::complete_tx::bytes [%0], [%1, {%3, %4}], [%2];"
                 :: "r"(dst), "l"(tm), "r"(bar), "r"(c0), "r"(c1) : "memory");
}
__device__ __forceinline__ void tma_st(const CUtensorMap* tm, uint32_t src, int c0, int c1) {
    asm volatile("cp.async.bulk.tensor.2d.global.shared::cta.bulk_group [%0, {%2, %3}], [%1];" :: "l"(tm), "r"(src), "r"(c0), "r"(c1) : "memory");
}
__device__ __forceinline__ void ldsm4(uint32_t a, uint32_t& r0, uint32_t& r1, uint32_t& r2, uint32_t& r3) {
    asm volatile("ldmatrix.sync.aligned.m8n8.x4.shared.b16 {%0,%1,%2,%3}, [%4];"
                 : "=r"(r0), "=r"(r1), "=r"(r2), "=r"(r3) : "r"(a) : "memory");
}
__device__ __forceinline__ void ldsm4t(uint32_t a, uint32_t& r0, uint32_t& r1, uint32_t& r2, uint32_t& r3) {
    asm volatile("ldmatrix.sync.aligned.m8n8.x4.trans.shared.b16 {%0,%1,%2,%3}, [%4];"
                 : "=r"(r0), "=r"(r1), "=r"(r2), "=r"(r3) : "r"(a) : "memory");
}
__device__ __forceinline__ void ldsm2t(uint32_t a, uint32_t& r0, uint32_t& r1) {
    asm volatile("ldmatrix.sync.aligned.m8n8.x2.trans.shared.b16 {%0,%1}, [%2];" : "=r"(r0), "=r"(r1) : "r"(a) : "memory");
}
__device__ __forceinline__ void stsm4t(uint32_t a, uint32_t r0, uint32_t r1, uint32_t r2, uint32_t r3) {
    asm volatile("stmatrix.sync.aligned.m8n8.x4.trans.shared.b16 [%0], {%1,%2,%3,%4};"
                 :: "r"(a), "r"(r0), "r"(r1), "r"(r2), "r"(r3) : "memory");
}
__device__ __forceinline__ void stsm2t(uint32_t a, uint32_t r0, uint32_t r1) {
    asm volatile("stmatrix.sync.aligned.m8n8.x2.trans.shared.b16 [%0], {%1,%2};" :: "r"(a), "r"(r0), "r"(r1) : "memory");
}
__device__ __forceinline__ void stsm4(uint32_t a, uint32_t r0, uint32_t r1, uint32_t r2, uint32_t r3) {
    asm volatile("stmatrix.sync.aligned.m8n8.x4.shared.b16 [%0], {%1,%2,%3,%4};" :: "r"(a), "r"(r0), "r"(r1), "r"(r2), "r"(r3) : "memory");
}
__device__ __forceinline__ void stsm2(uint32_t a, uint32_t r0, uint32_t r1) {
    asm volatile("stmatrix.sync.aligned.m8n8.x2.shared.b16 [%0], {%1,%2};" :: "r"(a), "r"(r0), "r"(r1) : "memory");
}
__device__ __forceinline__ uint32_t movm(uint32_t a) {
    uint32_t d; asm volatile("movmatrix.sync.aligned.m8n8.trans.b16 %0, %1;" : "=r"(d) : "r"(a)); return d;
}
__device__ __forceinline__ void mma16(float* c, uint32_t a0, uint32_t a1, uint32_t a2, uint32_t a3, uint32_t b0, uint32_t b1) {
    asm volatile("mma.sync.aligned.m16n8k16.row.col.f32.bf16.bf16.f32 {%0,%1,%2,%3}, {%4,%5,%6,%7}, {%8,%9}, {%0,%1,%2,%3};"
                 : "+f"(c[0]), "+f"(c[1]), "+f"(c[2]), "+f"(c[3]) : "r"(a0), "r"(a1), "r"(a2), "r"(a3), "r"(b0), "r"(b1));
}
__device__ __forceinline__ void mma8(float* c, uint32_t a0, uint32_t a1, uint32_t b0) {
    asm volatile("mma.sync.aligned.m16n8k8.row.col.f32.bf16.bf16.f32 {%0,%1,%2,%3}, {%4,%5}, {%6}, {%0,%1,%2,%3};"
                 : "+f"(c[0]), "+f"(c[1]), "+f"(c[2]), "+f"(c[3]) : "r"(a0), "r"(a1), "r"(b0));
}
__device__ __forceinline__ void wg_fence() { asm volatile("wgmma.fence.sync.aligned;" ::: "memory"); }
__device__ __forceinline__ void wg_commit() { asm volatile("wgmma.commit_group.sync.aligned;" ::: "memory"); }
template <int N> __device__ __forceinline__ void wg_wait() { asm volatile("wgmma.wait_group.sync.aligned %0;" :: "n"(N) : "memory"); }
__device__ __forceinline__ uint64_t mkdesc(uint32_t addr, uint32_t lbo, uint32_t sbo, uint32_t swz) {
    return (uint64_t)((addr & 0x3FFFF) >> 4) | ((uint64_t)(lbo >> 4) << 16) | ((uint64_t)(sbo >> 4) << 32) | ((uint64_t)swz << 62);
}
template <int BOFF, int SC>
__device__ __forceinline__ void wgmma_rs16(float* d, uint32_t a0, uint32_t a1, uint32_t a2, uint32_t a3, uint32_t blo) {
    asm volatile("{.reg .pred p; .reg .b32 l; .reg .b64 bd; setp.ne.b32 p, %14, 0; add.u32 l, %12, %13; mov.b64 bd, {l, 40};\n"
                 "wgmma.mma_async.sync.aligned.m64n16k16.f32.bf16.bf16 {%0,%1,%2,%3,%4,%5,%6,%7}, {%8,%9,%10,%11}, bd, p, 1, 1, 0;}"
                 : "+f"(d[0]), "+f"(d[1]), "+f"(d[2]), "+f"(d[3]), "+f"(d[4]), "+f"(d[5]), "+f"(d[6]), "+f"(d[7])
                 : "r"(a0), "r"(a1), "r"(a2), "r"(a3), "r"(blo), "n"(BOFF), "n"(SC));
}
template <int BOFF, int SC>
__device__ __forceinline__ void wgmma_rs32(float* d, uint32_t a0, uint32_t a1, uint32_t a2, uint32_t a3, uint32_t blo) {
    asm volatile("{.reg .pred p; .reg .b32 l; .reg .b64 bd; setp.ne.b32 p, %22, 0; add.u32 l, %20, %21; mov.b64 bd, {l, 0x40000040};\n"
                 "wgmma.mma_async.sync.aligned.m64n32k16.f32.bf16.bf16 "
                 "{%0,%1,%2,%3,%4,%5,%6,%7,%8,%9,%10,%11,%12,%13,%14,%15}, {%16,%17,%18,%19}, bd, p, 1, 1, 0;}"
                 : "+f"(d[0]), "+f"(d[1]), "+f"(d[2]), "+f"(d[3]), "+f"(d[4]), "+f"(d[5]), "+f"(d[6]), "+f"(d[7]),
                   "+f"(d[8]), "+f"(d[9]), "+f"(d[10]), "+f"(d[11]), "+f"(d[12]), "+f"(d[13]), "+f"(d[14]), "+f"(d[15])
                 : "r"(a0), "r"(a1), "r"(a2), "r"(a3), "r"(blo), "n"(BOFF), "n"(SC));
}
template <int AOFF, int BOFF, int SC>
__device__ __forceinline__ void wgmma_ss32(float* d, uint32_t alo, uint32_t blo) {
    asm volatile("{.reg .pred p; .reg .b32 l, m; .reg .b64 ad, bd; setp.ne.b32 p, %20, 0; add.u32 l, %16, %18; add.u32 m, %17, %19;\n"
                 "mov.b64 ad, {l, 0x40000040}; mov.b64 bd, {m, 0x40000040};\n"
                 "wgmma.mma_async.sync.aligned.m64n32k16.f32.bf16.bf16 "
                 "{%0,%1,%2,%3,%4,%5,%6,%7,%8,%9,%10,%11,%12,%13,%14,%15}, ad, bd, p, 1, 1, 1, 0;}"
                 : "+f"(d[0]), "+f"(d[1]), "+f"(d[2]), "+f"(d[3]), "+f"(d[4]), "+f"(d[5]), "+f"(d[6]), "+f"(d[7]),
                   "+f"(d[8]), "+f"(d[9]), "+f"(d[10]), "+f"(d[11]), "+f"(d[12]), "+f"(d[13]), "+f"(d[14]), "+f"(d[15])
                 : "r"(alo), "r"(blo), "n"(AOFF), "n"(BOFF), "n"(SC));
}
template <int AOFF, int BOFF, int SC>
__device__ __forceinline__ void wgmma_ss8(float* d, uint32_t alo, uint32_t blo) {
    asm volatile("{.reg .pred p; .reg .b32 l, m; .reg .b64 ad, bd; setp.ne.b32 p, %8, 0; add.u32 l, %4, %6; add.u32 m, %5, %7;\n"
                 "mov.b64 ad, {l, 0x40000040}; mov.b64 bd, {m, 0};\n"
                 "wgmma.mma_async.sync.aligned.m64n8k16.f32.bf16.bf16 {%0,%1,%2,%3}, ad, bd, p, 1, 1, 1, 1;}"
                 : "+f"(d[0]), "+f"(d[1]), "+f"(d[2]), "+f"(d[3]) : "r"(alo), "r"(blo), "n"(AOFF), "n"(BOFF), "n"(SC));
}
template <int OFF, int SC>
__device__ __forceinline__ void wgmma_ss40(float* d, uint32_t alo, uint32_t blo) {
    asm volatile("{.reg .pred p; .reg .b32 l, m; .reg .b64 ad, bd; setp.ne.b32 p, %23, 0; add.u32 l, %20, %22; add.u32 m, %21, %22;\n"
                 "mov.b64 ad, {l, 0x40000020}; mov.b64 bd, {m, 0x40000040};\n"
                 "wgmma.mma_async.sync.aligned.m64n40k16.f32.bf16.bf16 "
                 "{%0,%1,%2,%3,%4,%5,%6,%7,%8,%9,%10,%11,%12,%13,%14,%15,%16,%17,%18,%19}, ad, bd, p, 1, 1, 0, 0;}"
                 : "+f"(d[0]), "+f"(d[1]), "+f"(d[2]), "+f"(d[3]), "+f"(d[4]), "+f"(d[5]), "+f"(d[6]), "+f"(d[7]),
                   "+f"(d[8]), "+f"(d[9]), "+f"(d[10]), "+f"(d[11]), "+f"(d[12]), "+f"(d[13]), "+f"(d[14]), "+f"(d[15]),
                   "+f"(d[16]), "+f"(d[17]), "+f"(d[18]), "+f"(d[19])
                 : "r"(alo), "r"(blo), "n"(OFF), "n"(SC));
}
template <int I> using IC = std::integral_constant<int, I>;
template <int I, int N, class F> __device__ __forceinline__ void static_for(F&& f) {
    if constexpr (I < N) { f(std::integral_constant<int, I>{}); static_for<I + 1, N>(f); }
}
__device__ __forceinline__ uint32_t mapa(uint32_t a, uint32_t rank) {
    uint32_t r, c; asm("mov.u32 %0, %%cluster_ctarank;" : "=r"(c));
    asm("mapa.shared::cluster.u32 %0, %1, %2;" : "=r"(r) : "r"(a), "r"(rank + (c > 2 ? 3 : 0))); return r;
}
__device__ __forceinline__ void st_async2(uint32_t a, uint32_t x, uint32_t y, uint32_t bar) {
    asm volatile("st.async.weak.shared::cluster.mbarrier::complete_tx::bytes.v2.b32 [%0], {%1,%2}, [%3];"
                 :: "r"(a), "r"(x), "r"(y), "r"(bar) : "memory");
}
__device__ __forceinline__ void st_async1(uint32_t a, uint32_t x, uint32_t bar) {
    asm volatile("st.async.weak.shared::cluster.mbarrier::complete_tx::bytes.b32 [%0], %1, [%2];" :: "r"(a), "r"(x), "r"(bar) : "memory");
}
__device__ __forceinline__ void st_async4(uint32_t a, uint32_t x, uint32_t y, uint32_t z, uint32_t w, uint32_t bar) {
    asm volatile("st.async.weak.shared::cluster.mbarrier::complete_tx::bytes.v4.b32 [%0], {%1,%2,%3,%4}, [%5];"
                 :: "r"(a), "r"(x), "r"(y), "r"(z), "r"(w), "r"(bar) : "memory");
}
__device__ __forceinline__ void sts2(uint32_t a, uint32_t x, uint32_t y) {
    asm volatile("st.shared.v2.b32 [%0], {%1,%2};" :: "r"(a), "r"(x), "r"(y) : "memory");
}
__device__ __forceinline__ void sts4(uint32_t a, uint4 v) {
    asm volatile("st.shared.v4.b32 [%0], {%1,%2,%3,%4};" :: "r"(a), "r"(v.x), "r"(v.y), "r"(v.z), "r"(v.w) : "memory");
}
__device__ __forceinline__ void sts1(uint32_t a, uint32_t x) { asm volatile("st.shared.b32 [%0], %1;" :: "r"(a), "r"(x) : "memory"); }
__device__ __forceinline__ float2 lds2f(uint32_t a) {
    float2 v; asm volatile("ld.shared.v2.f32 {%0,%1}, [%2];" : "=f"(v.x), "=f"(v.y) : "r"(a) : "memory"); return v;
}
__device__ __forceinline__ uint4 lds4(uint32_t a) {
    uint4 v; asm volatile("ld.shared.v4.b32 {%0,%1,%2,%3}, [%4];" : "=r"(v.x), "=r"(v.y), "=r"(v.z), "=r"(v.w) : "r"(a) : "memory"); return v;
}
__device__ __forceinline__ uint32_t lds1(uint32_t a) {
    uint32_t v; asm volatile("ld.shared.b32 %0, [%1];" : "=r"(v) : "r"(a) : "memory"); return v;
}
__device__ __forceinline__ void stg1(void* p, uint32_t x) { asm volatile("st.global.b32 [%0], %1;" :: "l"(p), "r"(x) : "memory"); }
__device__ __forceinline__ uint32_t ld_acquire(const uint32_t* p) {
    uint32_t v; asm volatile("ld.acquire.gpu.global.u32 %0, [%1];" : "=r"(v) : "l"(p) : "memory"); return v;
}
__device__ __forceinline__ uint32_t ld_relaxed(const void* p) {
    uint32_t v; asm volatile("ld.relaxed.gpu.global.u32 %0, [%1];" : "=r"(v) : "l"(p) : "memory"); return v;
}
__device__ __forceinline__ uint32_t ld_epoch() {
    uint32_t v; asm volatile("ld.relaxed.gpu.global.u32 %0, [%1];" : "=r"(v) : "l"(&g_epoch) : "memory"); return v + 1;
}
__device__ __forceinline__ void st_release(uint32_t* p, uint32_t v) { asm volatile("st.release.gpu.global.u32 [%0], %1;" :: "l"(p), "r"(v) : "memory"); }
__device__ __forceinline__ void st_pkt8(const void* p, uint32_t x, uint32_t y) {
    asm volatile("{.reg .b64 v; mov.b64 v, {%1,%2}; st.relaxed.gpu.global.b64 [%0], v;}" :: "l"(p), "r"(x), "r"(y) : "memory");
}
__device__ __forceinline__ void st_pkt4(const void* p, uint32_t x) {
    asm volatile("st.relaxed.gpu.global.b32 [%0], %1;" :: "l"(p), "r"(x) : "memory");
}
__device__ __forceinline__ uint4 ld_pkt(const void* p) {
    uint4 r;
    asm volatile("{.reg .b64 lo, hi; .reg .b128 v; ld.relaxed.gpu.global.b128 v, [%4]; mov.b128 {lo, hi}, v;\n"
                 "mov.b64 {%0,%1}, lo; mov.b64 {%2,%3}, hi;}"
                 : "=r"(r.x), "=r"(r.y), "=r"(r.z), "=r"(r.w) : "l"(p) : "memory");
    return r;
}

template <int OFF> __device__ __forceinline__ void ld_pkt8(uint32_t& x, uint32_t& y, const void* p) {
    asm volatile("{.reg .b64 v; ld.relaxed.gpu.global.b64 v, [%2 + %3]; mov.b64 {%0,%1}, v;}" : "=r"(x), "=r"(y) : "l"(p), "n"(OFF) : "memory");
}
template <int OFF> __device__ __forceinline__ void ld_pkt8_stale(uint32_t& x, uint32_t& y, const void* p, uint32_t tag) {
    asm volatile("{.reg .pred p; .reg .b32 t; .reg .b64 v; lop3.b32 t, %0, %3, 1, 0x28; setp.ne.u32 p, t, 0; mov.b64 v, {%0,%1};\n"
                 "@p ld.relaxed.gpu.global.b64 v, [%2 + %4]; mov.b64 {%0,%1}, v;}" : "+r"(x), "+r"(y) : "l"(p), "r"(tag), "n"(OFF) : "memory");
}
template <int OFF> __device__ __forceinline__ void ld_pkt_stale(uint4& r, const void* p, uint32_t tag) {
    asm volatile("{.reg .pred p; .reg .b32 t; .reg .b64 lo, hi; .reg .b128 v; lop3.b32 t, %0, %5, 1, 0x28; setp.ne.u32 p, t, 0;\n"
                 "mov.b64 lo, {%0,%1}; mov.b64 hi, {%2,%3}; mov.b128 v, {lo, hi}; @p ld.relaxed.gpu.global.b128 v, [%4 + %6];\n"
                 "mov.b128 {lo, hi}, v; mov.b64 {%0,%1}, lo; mov.b64 {%2,%3}, hi;}"
                 : "+r"(r.x), "+r"(r.y), "+r"(r.z), "+r"(r.w) : "l"(p), "r"(tag), "n"(OFF) : "memory");
}

constexpr int NX = 7;
constexpr uint32_t SB0 = 1024;
constexpr uint32_t HALF = 40960, OFF_WV = 0, OFF_WO = 81920, OFF_QX = OFF_WO + 36864, OFF_Q0 = OFF_WO + 90112, OFF_K0 = OFF_Q0 + 1024,
                   OFF_XR = OFF_K0 + 1024, OFF_SX = OFF_XR + NX * 4096, OFF_OX = OFF_SX, OFF_PX = OFF_SX + 5120, OFF_VM = OFF_SX,
                   OFF_SP = OFF_PX + 2560, OFF_Q1 = OFF_SP + 2560, OFF_K1 = OFF_Q1 + 1024, OFF_KX = OFF_K1 + 1024,
                   OFF_MEMT = OFF_KX + 4096, OFF_SM = OFF_MEMT + 10240, OFF_PM = OFF_SM + 1280, OFF_BAR = OFF_PM + 768,
                   OFF_DBG = OFF_BAR + 320, CHAIN_SMEM = OFF_DBG + 704,
                   OFF_SXL = OFF_XR, OFF_OXL = OFF_SXL, OFF_OXG = OFF_XR + 9216, OFF_TRED = OFF_WV + 65536, OFF_OXE = OFF_WV + 32768;
static_assert(OFF_Q1 == OFF_Q0 + HALF && CHAIN_SMEM <= 232448, "layout");
__host__ __device__ constexpr uint32_t wo_b(uint32_t j) { return OFF_WO + 24576 + j * 6144 + (j > 1 ? 28672 : 0); }
__host__ __device__ constexpr uint32_t tile_b(uint32_t u) { return u + (u < 8 ? 12 : 24); }
__host__ __device__ constexpr uint32_t xblk(int kb) { return kb < 3 ? OFF_MEMT - OFF_XR + kb * 4096 : (kb - 3) * 4096; }
constexpr uint32_t MB_S = OFF_BAR, MB_SX = OFF_BAR + 8, MB_O = OFF_BAR + 16, MB_WO = OFF_BAR + 24, MB_XA = OFF_BAR + 32,
                   MB_XB = OFF_BAR + 40, MB_EN = OFF_BAR + 80, MB_EM = OFF_BAR + 88, MB_EA = OFF_BAR + 96, OFF_ZERO = OFF_BAR + 112, OFF_EP = OFF_BAR + 116, OFF_KP = OFF_BAR + 120,
                   MB_F = OFF_BAR + 128, MB_E = OFF_BAR + 168, OFF_INV = OFF_BAR + 224, OFF_PRB = OFF_BAR + 256, OFF_TG = OFF_BAR + 264, MB_G = OFF_BAR + 272, OFF_RL = OFF_BAR + 48, MB_H = MB_G + 32,
                   OFF_R0 = OFF_SP + 512, OFF_R1 = OFF_Q0;
constexpr int BAR_K = 0, BAR_PUB = 1, BAR_QK = 2, BAR_P = 3, BAR_WO = 4, BAR_S = 5, BAR_V = 6, BAR_O = 7, BAR_R = 8, BAR_PM = 9, BAR_SX = 10,
              BAR_Q = 11, BAR_X = 15, BAR_QJ = BAR_O, BAR_SR = 12, BAR_OR = 13, BAR_OF = 14;
__host__ __device__ constexpr int bar_g(int i, int w) { return i + w < 2 ? 12 + 2 * i + w : BAR_PM; }
constexpr float SCL_B = 0.07216878364870322f * 1.4426950408889634f;
#ifndef DEFN
#define DEFN 1
#endif
#ifndef ZG
#define ZG 1
#endif
#ifndef NAC
#define NAC 3
#endif
#ifndef WOE
#define WOE 1
#endif
#ifndef TX0
#define TX0 2
#endif
#ifndef PATT
#define PATT "UUUUUUOURUUOURUOURUOURUOUROROROROORR"
#endif
#ifndef HOME
#define HOME 1
#endif
#ifndef SW
#define SW 3
#endif
#ifndef NPROBE
#define NPROBE 3
#endif
#ifdef TUNE
__constant__ int c_tune[16];
extern "C" void tune_set(const int* v) { cudaMemcpyToSymbol(c_tune, v, 64); }
#define DLY1 c_tune[0]
#define STG1 c_tune[1]
#define STG2 c_tune[2]
#define STG3 c_tune[3]
#define STG4 c_tune[4]
#define H0 c_tune[5]
#define H1 c_tune[6]
#define H2 c_tune[7]
#define H3 c_tune[8]
#define DLYN c_tune[9]
#define HS c_tune[10]
#define KPT c_tune[11]
#define H4 c_tune[12]
#endif
#ifndef STG1
#define STG1 310
#endif
#ifndef KPT
#define KPT 0x99
#endif
#ifndef DLYN
#define DLYN 470
#endif
#ifndef DLY1
#define DLY1 1400
#endif
#ifndef STG2
#define STG2 110
#endif
#ifndef STG3
#define STG3 280
#endif
#ifndef STG4
#define STG4 300
#endif
#ifndef OPT
#define OPT 1
#endif
#ifndef PVB
#define PVB 1
#endif
#ifndef HS
#define HS 0
#endif
#ifndef XG
#define XG 2
#endif
#ifndef EAS
#define EAS 0
#endif
#ifndef BJ
#define BJ 3
#endif
#ifndef CJ
#define CJ 7
#endif
#ifndef OJ
#define OJ 9
#endif
#ifndef H4
#define H4 830
#endif
#ifndef H0
#define H0 2690
#endif
#ifndef H1
#define H1 2710
#endif
#ifndef H2
#define H2 3040
#endif
#ifndef H3
#define H3 2980
#endif
#ifndef NVC
#define NVC 4
#endif
#ifndef PWIN
#define PWIN 3
#endif
#ifndef KP0
#define KP0 5
#endif
#ifndef FNC
#define FNC 1
#endif
#ifndef VG
#define VG 0
#endif
#ifndef EMW
#define EMW 1
#endif
#ifndef SJ
#define SJ 9
#endif
#ifndef WP
#define WP 0
#endif
#ifndef VW
#define VW 1
#endif
#ifndef VN
#define VN 0
#endif
#ifndef MG
#define MG 1
#endif
#ifndef WE
#define WE 1
#endif
#ifndef RM
#define RM 1
#endif
#ifndef VE
#define VE 2
#endif
#ifndef OD
#define OD 2
#endif
#ifndef WS
#define WS 1
#endif
#ifndef PAUSE
#define PAUSE 0
#endif
#ifndef XO
#define XO 0
#endif
#ifndef VL
#define VL 0
#endif
#ifndef GS
#define GS 1
#endif
#ifndef TG
#define TG 1
#endif
#ifndef XC
#define XC 0
#endif
#ifndef PFX
#define PFX 1
#endif
#ifndef AE
#define AE 4
#endif
#ifndef SR
#define SR 1
#endif
#ifndef W1
#define W1 4
#endif
#ifndef W2
#define W2 W1
#endif
#ifndef W0
#define W0 0
#endif
#ifndef CL
#define CL 6
#endif
#ifndef BT
#define BT 1
#endif
#ifndef PF
#define PF 0
#endif
#ifndef LAG
#define LAG 3
#endif
#ifndef OP
#define OP 1
#endif
#ifndef CD
#define CD 1
#endif
#ifndef AP
#define AP 1
#endif
#ifndef AQ
#define AQ 0
#endif
#ifndef XR
#define XR 1
#endif
#ifndef BP
#define BP 0
#endif
#ifndef VS
#define VS 0
#endif
#ifndef XW
#define XW 0
#endif
#ifndef VD
#define VD 2
#endif

__device__ __forceinline__ uint32_t clk32() { uint32_t c; asm volatile("mov.u32 %0, %%clock;" : "=r"(c)); return c; }
__device__ __forceinline__ void spin(uint32_t n) { const uint32_t t = clk32(); while (clk32() - t < n) { } }
__device__ __forceinline__ uint32_t gtime() { uint64_t c; asm volatile("mov.u64 %0, %%globaltimer;" : "=l"(c)); return (uint32_t)c; }
__device__ __forceinline__ uint32_t clkv() { uint64_t c; asm volatile("mov.u64 %0, %%clock64;" : "=l"(c)); return (uint32_t)c; }
__device__ __forceinline__ void gate(uint32_t t) { while ((int)(clk32() - t) < 0) { } }
__device__ __forceinline__ void gatev(uint32_t t) { while ((int)(clkv() - t) < 0) { } }
__device__ __forceinline__ uint32_t keep(uint32_t x) { asm volatile("" : "+r"(x)); return x; }
template <class T> __device__ __forceinline__ T* keepp(T* p) { asm volatile("" : "+l"(p)); return p; }
__device__ __forceinline__ void sched() { asm volatile("bar.warp.sync 0xffffffff;" ::: "memory"); }
__device__ __forceinline__ void blk(int s) { asm volatile("{.reg .pred p; setp.gt.s32 p, %0, 1000; @p exit;}" :: "r"(s) : "memory"); }
__device__ __forceinline__ uint32_t selu(bool c, uint32_t a, uint32_t b) {
    uint32_t r; asm("{.reg .pred p; setp.ne.u32 p, %1, 0; selp.b32 %0, %2, %3, p;}" : "=r"(r) : "r"((uint32_t)c), "r"(a), "r"(b)); return r;
}
__device__ __forceinline__ float bf_lo(uint32_t w) { return __uint_as_float(w << 16); }
__device__ __forceinline__ float bf_hi(uint32_t w) { return __uint_as_float(w & 0xffff0000u); }
__device__ __forceinline__ uint32_t badd2(uint32_t a, uint32_t b) { uint32_t r; asm("add.rn.bf16x2 %0, %1, %2;" : "=r"(r) : "r"(a), "r"(b)); return r; }
__device__ __forceinline__ uint32_t tagx(uint32_t a, uint32_t b, uint32_t t) { uint32_t r; asm("lop3.b32 %0, %1, %2, %3, 0x7e;" : "=r"(r) : "r"(a), "r"(t), "r"(b)); return r; }
__device__ __forceinline__ uint32_t tagv(uint32_t a, uint32_t b, uint32_t t) { uint32_t r; asm volatile("lop3.b32 %0, %1, %2, %3, 0x7e;" : "=r"(r) : "r"(a), "r"(t), "r"(b)); return r; }
__device__ __forceinline__ uint32_t bit0(uint32_t a, uint32_t t) { uint32_t r; asm("lop3.b32 %0, %1, 0xfffffffe, %2, 0xe2;" : "=r"(r) : "r"(a), "r"(t)); return r; }
__device__ __forceinline__ uint32_t or3(uint32_t a, uint32_t b, uint32_t c) { uint32_t r; asm("lop3.b32 %0, %1, %2, %3, 0xfe;" : "=r"(r) : "r"(a), "r"(b), "r"(c)); return r; }
__device__ __forceinline__ bool any_bit0(uint32_t a, uint32_t b) {
    uint32_t r;
    asm volatile("{.reg .pred p; .reg .b32 t; lop3.b32 t, %1, 1, %2, 0xc8; setp.ne.u32 p, t, 0; vote.sync.any.pred p, p, 0xffffffff; selp.u32 %0, 1, 0, p;}"
                 : "=r"(r) : "r"(a), "r"(b));
    return r;
}
template <int N> __device__ __forceinline__ bool stale_or_arrive(uint32_t a, uint32_t b, uint32_t A) {
    uint32_t r;
    asm volatile("{.reg .pred p; .reg .b32 t; lop3.b32 t, %1, 1, %2, 0xc8; setp.ne.u32 p, t, 0; vote.sync.any.pred p, p, 0xffffffff;\n"
                 "@!p bar.arrive %3, %4; selp.u32 %0, 1, 0, p;}" : "=r"(r) : "r"(a), "r"(b), "r"(A), "n"(N) : "memory");
    return r;
}
template <int A> __device__ __forceinline__ bool bar_any(bool x) {
    uint32_t r;
    asm volatile("{.reg .pred p; setp.ne.u32 p, %1, 0; bar.red.or.pred p, %2, 128, p; selp.u32 %0, 1, 0, p;}" : "=r"(r) : "r"((uint32_t)x), "n"(A) : "memory");
    return r;
}
__device__ __forceinline__ uint4 ld_s4(uint32_t a) {
    uint4 v; asm volatile("ld.volatile.shared.v4.b32 {%0,%1,%2,%3}, [%4];" : "=r"(v.x), "=r"(v.y), "=r"(v.z), "=r"(v.w) : "r"(a) : "memory"); return v;
}
__device__ __forceinline__ void arrive_e(uint32_t bar) {
    asm volatile("{.reg .pred p; elect.sync _|p, 0xffffffff; @p mbarrier.arrive.shared::cta.b64 _, [%0];}" :: "r"(bar) : "memory");
}
__device__ __forceinline__ void expect_e(uint32_t bar, uint32_t bytes) {
    asm volatile("{.reg .pred p; elect.sync _|p, 0xffffffff; @p mbarrier.arrive.expect_tx.shared::cta.b64 _, [%0], %1;}" :: "r"(bar), "r"(bytes) : "memory");
}
__device__ __forceinline__ void tma2d_e(uint32_t dst, const CUtensorMap* tm, int c0, int c1, uint32_t bar) {
    asm volatile("{.reg .pred p; elect.sync _|p, 0xffffffff;\n"
                 "@p cp.async.bulk.tensor.2d.shared::cluster.global.mbarrier::complete_tx::bytes [%0], [%1, {%3, %4}], [%2];}"
                 :: "r"(dst), "l"(tm), "r"(bar), "r"(c0), "r"(c1) : "memory");
}
#ifdef DEV
__constant__ int g_s0;
#define DBGBASE const uint32_t dbg = sb + OFF_DBG + ((uint32_t)(s - g_s0) < 2 ? (s - g_s0) * 320 + warp * 20 : 640)
#ifdef GT
#define TSTAMP(i) do { if (GT >> (i) & 1) asm volatile("{.reg .b32 t; mov.u32 t, %%globaltimer_lo; st.shared.b16 [%0 + %1], t;}" :: "r"(dbg), "n"((i) * 2) : "memory"); } while (0)
#else
#define TSTAMP(i) asm volatile("{.reg .b32 t; mov.u32 t, %%clock; st.shared.b16 [%0 + %1], t;}" :: "r"(dbg), "n"((i) * 2) : "memory")
#endif
#define TVAL(i, v) asm volatile("st.shared.b16 [%0 + %1], %2;" :: "r"(dbg), "n"((i) * 2), "r"(v) : "memory")
#ifdef SST_
#define TS2(i) TSTAMP(i)
#define TS3(i) do { } while (0)
#else
#define TS2(i) do { } while (0)
#define TS3(i) TSTAMP(i)
#endif
#define TVAL0(i, v) g_cal[blockIdx.x * 8 + i] = v
__device__ __forceinline__ void calib(uint32_t* dst) {
    uint32_t g1, sm; asm volatile("mov.u32 %0, %%globaltimer_lo;" : "=r"(g1)); asm volatile("mov.u32 %0, %%smid;" : "=r"(sm));
    dst[0] = g1; dst[1] = clk32(); g_cal[blockIdx.x * 8 + 4] = sm;
}
__device__ uint32_t g_pp[132 * 32];
__device__ uint32_t g_off[132 * 2];
__global__ void calib_kernel() {
    uint32_t sm; asm volatile("mov.u32 %0, %%smid;" : "=r"(sm));
    if (threadIdx.x) return;
    if (sm == 0) {
        for (int i = 1; i < 132; i++) {
            uint32_t best = 0xffffffffu, off = 0;
            for (uint32_t r = 1; r <= 8; r++) {
                volatile uint32_t* l = g_pp + i * 32;
                const uint32_t t0 = clk32();
                l[0] = r;
                unsigned long long v = 0;
                for (int c = 0; c < 100000; c++) { v = *(volatile unsigned long long*)(l + 2); if ((uint32_t)v == r) break; }
                const uint32_t t1 = clk32();
                if (t1 - t0 < best) { best = t1 - t0; off = (uint32_t)(v >> 32) - (t0 + (t1 - t0) / 2); }
                spin(100 + 37 * r);
            }
            g_off[2 * i] = off; g_off[2 * i + 1] = best;
        }
        g_off[0] = 0; g_off[1] = 0;
    } else {
        volatile uint32_t* l = g_pp + sm * 32;
        for (uint32_t r = 1; r <= 8; r++) {
            for (int c = 0; c < 4000000; c++) if (l[0] == r) break;
            *(volatile unsigned long long*)(l + 2) = ((unsigned long long)clk32() << 32) | r;
        }
    }
}
#else
#define TS2(i) do { } while (0)
#define TS3(i) do { } while (0)
#define DBGBASE do { } while (0)
#define TSTAMP(i) do { } while (0)
#define TVAL(i, v) do { } while (0)
#define TVAL0(i, v) do { } while (0)
#endif

__device__ __forceinline__ uint32_t xch_page(uint32_t t, uint32_t h) { return t * 0x2000 + ((h ^ t ^ (t >> 3) ^ (t >> 4)) & 1) * 0x1000; }
constexpr uint32_t XCH_CLK = 0x148000;
__host__ __device__ constexpr uint32_t xch_mem(uint32_t t) { return 0x100000 + (t < 12 ? t * 256 : t < 20 ? 0x8000 + (t - 12) * 256 : t < 32 ? 0x4000 + (t - 20) * 256 : 0xc000 + (t - 32) * 256); }

__device__ __forceinline__ uint4 role_tab(uint32_t role, uint32_t side) {
    const uint32_t i = role >> 1, t = i < 12 ? i : i < 24 ? i + 8 : tile_b(i - 24);
    return make_uint4(xch_page(t, role & 1), xch_mem(t) + (role & 1) * 144, role < 48 ? DLY1 : role < 80 ? DLY1 + STG1 : 0, side * 4096);
}
constexpr unsigned long long PROG_MASK = 0xa222020202020200ull;
__device__ __forceinline__ bool prog_step(int s) { return PROG_MASK >> s & 1; }
__device__ __forceinline__ int pause_at(uint32_t role) { return role < 80 ? KPT >> (role < 48 ? 0 : 4) & 15 : 99; }

__device__ __forceinline__ void share_o(uint32_t sb, uint32_t rank, uint32_t src, uint32_t t) {
#pragma unroll
    for (uint32_t p = 1; p < 3; p++) {
        const uint32_t pb = mapa(sb, (rank + p) % 3);
        asm volatile("{.reg .pred p; elect.sync _|p, 0xffffffff;\n"
                     "@p cp.async.bulk.shared::cluster.shared::cta.mbarrier::complete_tx::bytes [%0], [%1], 4096, [%2];}"
                     :: "r"(pb + OFF_OXG + t * 8192 + (2 - p) * 4096), "r"(sb + src), "r"(pb + MB_F + 8 * t) : "memory");
    }
}

#define LANE_REGS const uint32_t l16 = __shfl_sync(0xffffffffu, sb + (tid & 31) * 16, tid & 31); const int lane = (l16 - sb) >> 4

__global__ void __cluster_dims__(CL, 1, 1) __launch_bounds__(512, 1)
chain_kernel(const __grid_constant__ CUtensorMap tmX, const __grid_constant__ CUtensorMap tmX7, const __grid_constant__ CUtensorMap tmWq, const __grid_constant__ CUtensorMap tmWk,
             const __grid_constant__ CUtensorMap tmWv, const __grid_constant__ CUtensorMap tmWo, const __grid_constant__ CUtensorMap tmWb,
             const __grid_constant__ CUtensorMap tmOx, const bf16* __restrict__ mem0, const char* xin,
             const char* win,
             bf16* out)
{
    extern __shared__ __align__(1024) uint8_t smem[];
    const uint32_t sb = smem_u32(smem);
    if ((sb & 0x3FFFF) != SB0) __trap();
    const int tid = threadIdx.x;
    const int warp = __shfl_sync(0xffffffffu, tid >> 5, 0);
    const uint32_t rank = blockIdx.x % 3;
    const int head = blockIdx.x / 3;
    uint32_t* const g_near = reinterpret_cast<uint32_t*>(g_near4);
    const char* pp = win + 0x140000 + (blockIdx.x & 63) * 64 + (blockIdx.x >> 6) * 0x4000;
    if (tid >= 480 && tid < 496) st_pkt4(pp + (tid & 8) * 512 + (tid & 7) * 4, 0);
    const uint32_t ep0 = ld_relaxed(&g_epoch);
    if (tid >= 320 && tid < 400) asm volatile("prefetch.global.L2 [%0];" :: "l"(mem0 + (tid - 320) * 64));

    if (tid == 384) {
        mbar_init(sb + MB_S, 3); mbar_init(sb + MB_SX, 1); mbar_init(sb + MB_O, 1); mbar_init(sb + MB_WO, 1);
        mbar_init(sb + MB_XA, 1); mbar_init(sb + MB_XB, 1); mbar_init(sb + MB_EM, 8); mbar_init(sb + MB_EN, 8); mbar_init(sb + MB_EA, 12);
        for (int i = 0; i < 5; i++) { mbar_init(sb + MB_F + 8 * i, 1); mbar_init(sb + MB_E + 8 * i, 8); mbar_init(sb + MB_G + 8 * i, 1); }
        sts1(sb + OFF_ZERO, 0);
        sts1(sb + OFF_KP, pause_at(blockIdx.x)); sts4(sb + OFF_RL, role_tab(blockIdx.x, 0));
        asm volatile("fence.mbarrier_init.release.cluster;" ::: "memory");
        asm volatile("fence.proxy.async.shared::cta;" ::: "memory");
        for (int i = 0; i < PWIN; i++) {
            mbar_expect(sb + MB_F + 8 * i, 32768);
            tma2d(sb + OFF_WV + i * 16384, &tmWq, head * DH + rank * 64, i * 128, sb + MB_F + 8 * i);
            tma2d(sb + OFF_WO + i * 16384, &tmWk, head * DH + rank * 64, i * 128, sb + MB_F + 8 * i);
        }
        mbar_expect(sb + MB_XA, 9 * 4096); mbar_expect(sb + MB_XB, 4096);
        for (int i = 0; i < 10; i++) tma2d(sb + OFF_XR + xblk(i), &tmX, i * 64, 0, sb + (i == 2 ? MB_XB : MB_XA));
        mbar_expect(sb + MB_WO, 49152 + (rank ? 5 : 6) * 6144);
    }
    TLC(10, 70);
    asm volatile("griddepcontrol.launch_dependents;" ::: "memory");
    TLC(9, 73);
    __syncthreads();
    asm volatile("barrier.cluster.arrive.release.aligned;" ::: "memory");

    if (warp < 8) {
        asm volatile("setmaxnreg.inc.sync.aligned.u32 208;");
        LANE_REGS;
        const int w4 = warp & 3;
        const uint32_t st0 = __shfl_sync(0xffffffffu, sb + (warp >> 2) * 40960 + ((lane & 7) + ((lane >> 4) << 3)) * 128 +
                                                      (((2 * w4 + ((lane >> 3) & 1)) ^ (lane & 7)) << 4), lane);
        const uint32_t xr_lo = (((SB0 + OFF_XR) & 0x3FFFF) >> 4) | (1u << 16);
        const uint32_t ta = (warp >> 2) * 20 + rank * 4 + w4, tb = tile_b(3 * warp + rank);
        const bool two = 3 * warp + rank < 16;
        const int wg = __reduce_max_sync(0xffffffffu, (unsigned)tid >> 7);
        const uint32_t uo = __reduce_max_sync(0xffffffffu, OFF_Q0 - 1024 - ((unsigned)tid >> 7) * 5120), ub = __reduce_max_sync(0xffffffffu, wo_b((unsigned)tid >> 5) - ((unsigned)tid >> 7) * 5120);
        uint32_t lm = __shfl_sync(0xffffffffu, sb + (warp >> 2) * 5120 + ((lane & 7) + ((lane >> 4) << 3)) * 32 + (((lane >> 3) ^ (lane >> 2)) & 1) * 16, lane);
        uint32_t wq[80], wk[80];
        {
            if (wg) { arrive_e(sb + MB_E); arrive_e(sb + MB_E + 8); } else { arrive_e(sb + MB_E + 24); arrive_e(sb + MB_E + 32); }
#pragma unroll
            for (int k = 0; k < 20; k++) {
                if (k % 4 == 0) mbar_wait(sb + MB_F + ((wg * 20 + k) >> 3) * 8, 0);
                ldsm4t(st0 + (OFF_WV + k * 2048), wq[4 * k], wq[4 * k + 1], wq[4 * k + 2], wq[4 * k + 3]);
                ldsm4t(st0 + (OFF_WO + k * 2048), wk[4 * k], wk[4 * k + 1], wk[4 * k + 2], wk[4 * k + 3]);
                if (k % 4 == 3 && (k == 19 || (k & 4) >> 2 != wg)) arrive_e(sb + MB_E + ((wg * 20 + k) >> 3) * 8);
            }
        }
        asm volatile("barrier.cluster.wait.acquire.aligned;" ::: "memory");
        mbar_wait(sb + MB_E + 16, 0);
        TLC(0, 71);
        mbar_wait(sb + MB_XA, 0);
        TLC(0, 72);

        uint32_t a[20][4];
#pragma unroll
        for (int k = 0; k < 16; k++) a[k >> 2][k & 3] = 0;

        for (int s = 0; ; s++) {
            DBGBASE;
            blk(warp);
            auto la = [&](int k) { ldsm4t(st0 + (OFF_WV + k * 2048), a[k][0], a[k][1], a[k][2], a[k][3]); blk(warp); };
            {
                auto bulk = [&](auto WG) {
                    constexpr int W = WG.value;
                    constexpr uint32_t own = (W ? OFF_KX : OFF_QX) - W * HALF, oth = (W ? OFF_QX : OFF_KX) - W * HALF;
                    float acc[16];
#pragma unroll
                    for (int i = 0; i < 16; i++) acc[i] = 0.f;
                    auto put = [&](uint32_t o) {
                        stsm4t(st0 + o, pack2(acc[0], acc[1]), pack2(acc[2], acc[3]), pack2(acc[4], acc[5]), pack2(acc[6], acc[7]));
                        stsm4t(st0 + (o + 2048), pack2(acc[8], acc[9]), pack2(acc[10], acc[11]), pack2(acc[12], acc[13]), pack2(acc[14], acc[15]));
                    };
                    uint32_t u[8];
                    auto get = [&]() {
                        bar_sync(W ? BAR_QJ : BAR_QK, 256);
                        ldsm4t(st0 + own, u[0], u[1], u[2], u[3]);
                        ldsm4t(st0 + (own + 2048), u[4], u[5], u[6], u[7]);
                    };
                    auto lv = [&](int k) { ldsm4t(st0 + (OFF_WV + k * 2048), a[k][0], a[k][1], a[k][2], a[k][3]); };
                    if constexpr (W && LAG) bar_sync(BAR_PUB, 256);
                    static_for<0, 10>([&](auto H) {
                        constexpr int h = H.value, kb = h < 5 ? (h + 3) % 5 : h - 5;
                        if constexpr (h == 5) {
                            if constexpr (W) get(); else { if (s > 0) bar_sync(BAR_SX, 256); }
                            wg_wait<0>();
                            put(oth);
                            bar_arrive(W ? BAR_QK : BAR_QJ, 256);
                            if constexpr (W) {
#pragma unroll
                                for (int i = 0; i < 8; i++) { acc[2 * i] = bf_lo(u[i]); acc[2 * i + 1] = bf_hi(u[i]); }
                            }
                        }
                        wg_fence();
                        static_for<0, 4>([&](auto K4) {
                            constexpr int k4 = K4.value, r = 16 * kb + 4 * k4;
                            const uint32_t* w = (h < 5) == W ? wq : wk;
#ifndef NOBULK
                            wgmma_rs32<xblk(5 * W + kb) / 16 + k4 * 2, ((W ? h : h % 5) | k4) != 0>(acc, w[r], w[r + 1], w[r + 2], w[r + 3], xr_lo);
#endif
                            if constexpr ((BT == 2 && k4 == 1) || (BT == 3 && k4 < 3)) { wg_commit(); wg_wait<1>(); wg_fence(); }
                        });
                        wg_commit();
                        if constexpr (h == 7) {
                            if (s == 0) {
#pragma unroll 1
                                for (int i = 0; i < 3; i++) mbar_wait_long(sb + MB_F + 8 * (2 * W + i), 1);
#pragma unroll
                                for (int k = 0; k < AE; k++) lv(k);
                            }
                        }
                        if constexpr (!W && LAG == 2 * h + 1) bar_arrive(BAR_PUB, 256);
                        if constexpr (AP && h >= AP - 1 && h < AP + 1) { if constexpr (W || !AQ) { lv(2 * (h - AP + 1)); lv(2 * (h - AP + 1) + 1); } }
                        if constexpr (h == 3 && !W) mbar_wait(sb + MB_XB, s & 1);
                        if constexpr (h == 9 && !W) get();
                        if constexpr (h != 4 && h != 9) wg_wait<1>();
                        if constexpr (!W && LAG == 2 * h + 2) bar_arrive(BAR_PUB, 256);
                        if constexpr (h == 7 && !W) arrive_e(sb + MB_EM);
                        if constexpr (h == 7) TSTAMP(9);
                        if constexpr (h == 0) TSTAMP(6);
                        if constexpr (h == 8 && !W) arrive_e(sb + MB_EN);
                    });
                    wg_wait<0>();
                    if constexpr (!W) {
#pragma unroll
                        for (int i = 0; i < 8; i++) { acc[2 * i] += bf_lo(u[i]); acc[2 * i + 1] += bf_hi(u[i]); }
                    }
                    put(own);
#pragma unroll
                    for (int k = AP && AQ && !W ? 0 : AE; k < 4; k++) lv(k);
                };
                if (__builtin_expect(wg == 0, 1)) bulk(IC<0>()); else bulk(IC<1>());
                arrive_e(sb + MB_EA);
                TSTAMP(0);
            }
            uint32_t f[12][4];
            auto ld = [&](int n) { ldsm4t(st0 + (OFF_WO + n * 2048), f[n][0], f[n][1], f[n][2], f[n][3]); };
            {
                float qa[4] = {0, 0, 0, 0}, qb[4] = {0, 0, 0, 0}, ka[4] = {0, 0, 0, 0}, kb[4] = {0, 0, 0, 0}, cu[4] = {0, 0, 0, 0}, cv[4] = {0, 0, 0, 0};
                uint32_t b[10][4], u0, u1;
                auto grp = [&](int i) { if (wg) bar_sync(bar_g(i, 1), 160); else bar_sync(bar_g(i, 0), 160); };
                auto lb = [&](int j) { ldsm4t(lm + (OFF_MEMT + j * 512), b[j][0], b[j][1], b[j][2], b[j][3]); blk(warp); };
                auto mm = [&](float* c, const uint32_t* w, int k) { mma16(c, w[0], w[1], w[2], w[3], b[k >> 1][2 * (k & 1)], b[k >> 1][2 * (k & 1) + 1]); blk(warp); };
                auto mq = [&](int k) { mm(k & 1 ? qb : qa, wq + 4 * k, k); };
                auto mk = [&](int k) { mm(k & 1 ? kb : ka, wk + 4 * k, k); };
                auto mu = [&](int k) { mm(cu, a[k], k); };
                blk(warp);
                grp(0);
                lb(0); lb(1);
                mu(0); TSTAMP(1); mq(0); mk(0); mq(1); mu(1); mk(1); lb(2);
                mq(2); mk(2); mu(2); la(4); mq(3); mk(3); mu(3); lb(3); la(5);
                mq(4); mk(4); mq(5); mu(4); la(6); mk(5); mq(6); mu(5); lb(4); la(7);
                mk(6); mq(7); mu(6); lb(5); mk(7); mq(8); mq(9); mu(7);
                grp(1); TSTAMP(8); lb(6); lb(7); mk(8); mq(10); mk(9); mq(11);
                u0 = pack2(cu[0], cu[1]); u1 = pack2(cu[2], cu[3]); blk(warp);
                mq(12); mk(10); mq(13); mk(11);
                lb(8); lb(9);
                mq(14); mk(12); mq(15); mk(13); mq(16); mq(17); mk(14); mq(18); mq(19); mk(15); mk(16);
                stsm2t(st0 + OFF_Q0, pack2(qa[0] + qb[0], qa[1] + qb[1]), pack2(qa[2] + qb[2], qa[3] + qb[3]));
                bar_arrive(BAR_Q, 352);
                TS2(0);
                blk(warp);
                mk(17); mk(18);
#pragma unroll
                for (int k = 8; k < 8 + VE; k++) la(k);
                mk(19);
                stsm2t(st0 + OFF_K0, pack2(ka[0] + kb[0], ka[1] + kb[1]), pack2(ka[2] + kb[2], ka[3] + kb[3]));
                bar_arrive(BAR_K, 416);
                TSTAMP(2);
                auto rest = [&](auto TWO) {
                    constexpr bool T2 = TWO.value;
                    uint32_t l16, pw, sr, da, va, zr;
                    blk(warp);
                    asm volatile("shr.u32 %0, %1, 8;" : "=r"(zr) : "r"(s));
                    cv[0] = bf_lo(u0); cv[1] = bf_hi(u0); cv[2] = bf_lo(u1); cv[3] = bf_hi(u1);
#pragma unroll
                    for (int k = 8; k < 8 + VE; k++) mm(cv, a[k], k);
                    bar_sync(BAR_S, 288);
#pragma unroll
                    for (int k = 8 + VE; k < 8 + VE + VD; k++) la(k);
                    { const uint32_t o = lm + zr; l16 = keep(sb + ((o >> 1) & 112) + (((o << 3) ^ o) & 128) + (o & 256)); blk(warp); }
#pragma unroll
                    for (int k = 8 + VE; k < (VL ? 20 - VD : 20); k++) {
                        mm(cv, a[k], k);
                        if (k + VD < 20) la(k + VD); else if (k + VD - 20 < W0) { ld(k + VD - 20); blk(warp); }
                        if (k == 11) { const uint32_t ln = (l16 >> 4) & 31; sr = keep(sb + OFF_SM + warp * 160 + min(ln, 19u) * 8); blk(warp); }
                        if (k == 12) { const uint32_t ln = (l16 >> 4) & 31, pb = warp * 32 + (ln & 3) * 8; pw = keep(sb + OFF_PM + selu(ln < 4, pb, 2 * pb + 252 + (ln & 28))); blk(warp); }
                        if (k == 14) {
                            const uint32_t o = l16 - sb, e = ((o >> 1) & 127) + ((o & 256) << 4);
                            da = keep(e ^ (xch_page(ta, 0) + head * 128 + (head & 7) * 16));
                            blk(warp);
                        }
                        if (k == 15) { va = keep((l16 >> 1) + (sb - (sb >> 1) + OFF_VM) + warp * 256); blk(warp); }
                    }
                    if (!VL) {
                        sts2(va, pack2(cv[0], cv[1]), pack2(cv[2], cv[3]));
                        bar_arrive(BAR_V, 384);
                        blk(warp);
                    }
                    bar_sync(BAR_SR, 288);
                    TSTAMP(4);
                    const float2 u = lds2f(sr), v = lds2f(sr + (OFF_SP - OFF_SM)), w = lds2f(sr + (OFF_SP + 1280 - OFF_SM));
                    blk(warp);
#pragma unroll
                    for (int k = 20 - VD; k < 20; k++) if (VL) mm(cv, a[k], k);
                    float x = u.x + v.x + w.x, y = u.y + v.y + w.y;
                    int m = __float_as_int(fmaxf(x, y));
                    m ^= (m >> 31) & 0x7fffffff;
                    blk(warp);
                    m = __reduce_max_sync(0xffffffffu, m);
                    if (VL) { sts2(va, pack2(cv[0], cv[1]), pack2(cv[2], cv[3])); bar_arrive(BAR_V, 384); }
#pragma unroll
                    for (int n = W0; n < W1; n++) ld(n);
                    m ^= (m >> 31) & 0x7fffffff;
                    const float mx = __int_as_float(m) * -SCL_B;
                    x = ex2(fmaf(x, SCL_B, mx)); y = ex2(fmaf(y, SCL_B, mx));
                    if (l16 < sb + 320) sts1(pw, pack2(x, y));
                    bar_arrive(BAR_PM, 384);
                    blk(warp);
                    const uint32_t tag = lds1(sb + OFF_EP) ^ s;
                    const uint32_t fx = __reduce_add_sync(0xffffffffu, l16 < sb + 320 ? __float_as_uint((x + y) + 8.f) - 0x41000000u : 0u);
                    const float fs = __uint2float_rn(fx);
                    blk(warp);
#pragma unroll
                    for (int n = W1; n < W2; n++) ld(n);
                    blk(warp);
                    sts1(sb + OFF_INV + warp * 4, bit0(__float_as_uint(rcpf(fs) * 1048576.f), tag + l16));
                    TSTAMP(5);
                    if (s == NSEG - 1) return true;
                    const uint32_t ia = keep(sb + OFF_INV + ((keep(l16) >> 1) & 24));
                    uint32_t bb[6][4], g[12][4];
                    float ca[4] = {0, 0, 0, 0}, cb[4] = {0, 0, 0, 0}, cd[4] = {0, 0, 0, 0}, ce[4] = {0, 0, 0, 0};
                    auto lo = [&](int j) { ldsm4t(lm + uo + ((j < 2 ? HALF + 1024 : 0) + j * 512), bb[j][0], bb[j][1], bb[j][2], bb[j][3]); blk(warp); };
                    auto lf = [&](int n) { if (n >= W2) { ld(n); blk(warp); } };
                    auto lg = [&](int n) { if (T2 && n < 12) { ldsm4t(lm + ub + n * 512, g[n][0], g[n][1], g[n][2], g[n][3]); blk(warp); } };
                    auto ma = [&](float* c, int n) { mma16(c, f[n][0], f[n][1], f[n][2], f[n][3], bb[n >> 1][2 * (n & 1)], bb[n >> 1][2 * (n & 1) + 1]); blk(warp); };
                    auto mb = [&](float* c, int n) { if (T2) { mma16(c, g[n][0], g[n][1], g[n][2], g[n][3], bb[n >> 1][2 * (n & 1)], bb[n >> 1][2 * (n & 1) + 1]); blk(warp); } };
                    lm = keep(lm);
                    blk(warp);
                    bar_sync(BAR_O, 384);
                    lo(0); lo(1);
#if OP == 0
                    lf(0); lf(1); lf(2); lf(3); lf(4); lf(5); lf(6);
                    ma(ca, 0); ma(cd, 1); ma(ca, 2); lg(0); ma(cd, 3); lg(1);
                    mb(cb, 0); mb(cb, 1); lg(2); lg(3); mb(cb, 2); lf(7);
#else
                    lg(0); lg(1); lg(2);
                    ma(ca, 0); ma(ca, 1); lg(3); mb(cb, 0); ma(ca, 2); lf(4); mb(cb, 1); lf(5); ma(ca, 3); lf(6); lf(7); mb(cb, 2); lf(8);
#endif
                    const float2 inv = lds2f(ia);
                    auto st = [&](const float* c, const float* d, uint32_t o) {
                        st_pkt8(win + o, bit0(pack2((c[0] + d[0]) * inv.x, (c[1] + d[1]) * inv.y), __float_as_uint(inv.x)), pack2((c[2] + d[2]) * inv.x, (c[3] + d[3]) * inv.y));
                        blk(warp);
                    };
                    mb(cb, 3);
                    bar_sync(BAR_OR, 288);
                    lo(2); lo(3);
#if OP == 0
                    ma(ca, 4); lf(8); ma(cd, 5); lo(4); ma(ca, 6); lf(9); ma(cd, 7); lo(5); ma(ca, 8); lf(10); ma(cd, 9); lf(11);
                    ma(ca, 10); lg(4); ma(cd, 11); lg(5);
#else
                    ma(ca, 4); lo(4); ma(ca, 5); lf(9); ma(ca, 6); lo(5); ma(ca, 7); lf(10); ma(ca, 8); lf(11); ma(ca, 9); lg(4);
                    ma(cd, 10); ma(ca, 11); lg(5);
#endif
                    st(ca, cd, da);
                    bar_arrive(BAR_OF, 288);
                    TSTAMP(3);
                    if constexpr (T2) {
                        lg(6); lg(7);
                        mb(cb, 4); lg(8); mb(ce, 5); lg(9); mb(cb, 6); lg(10); mb(ce, 7); lg(11); mb(cb, 8); mb(ce, 9); mb(cb, 10); mb(ce, 11);
                        st(cb, ce, da ^ (xch_page(ta, 0) ^ xch_page(tb, 0)));
                    }
#pragma unroll
                    for (int k = 0; k < AE; k++) if (!AP) la(k);
                    return false;
                };
                if (two ? rest(IC<1>()) : rest(IC<0>())) break;
            }
            TSTAMP(7);
            if (WS) bar_sync(BAR_WO, 384); else bar_arrive(BAR_WO, 384);
        }
        TLC(0, 65);
        asm volatile("setmaxnreg.dec.sync.aligned.u32 168;");
        uint32_t f[24][4];
        uint32_t lnt; asm volatile("mov.u32 %0, %%laneid;" : "=r"(lnt));
        {
            const uint32_t sbb = sb + wo_b(two ? warp : 0) + ((lnt & 7) + ((lnt >> 4) << 3)) * 32 + (((lnt >> 3) ^ (lnt >> 2)) & 1) * 16;
#pragma unroll
            for (int n = 0; n < 12; n++) {
                ldsm4t(st0 + (OFF_WO + n * 2048), f[n][0], f[n][1], f[n][2], f[n][3]);
                ldsm4t(sbb + n * 512, f[12 + n][0], f[12 + n][1], f[12 + n][2], f[12 + n][3]);
            }
        }
        bar_sync(BAR_QK, 256);
        TLC(0, 67);
        const uint32_t ep = lds1(sb + OFF_EP);
        char* tp = reinterpret_cast<char*>(g_tail) + head * 40960;
        uint32_t ts = sb + OFF_WV + warp * 2048;
        const uint32_t o16 = lnt * 16;
#pragma unroll 1
        for (int t = 0; t < 4; t++) {
            const uint32_t b0 = ((SB0 + (t < 2 ? OFF_OXE + t * 12288 : t == 3 ? OFF_OXL : OFF_OX)) >> 4) | (1u << 16);
            const uint32_t b1 = t < 2 ? b0 + 256 : ((SB0 + OFF_OXG + (t - 2) * 8192) >> 4) | (1u << 16);
            float acc[2][16];
#pragma unroll
            for (int i = 0; i < 16; i++) acc[0][i] = acc[1][i] = 0.f;
            auto st = [&](int i, uint32_t blkc) {
                const float* a = acc[i];
                sts4(ts + o16 + i * 1024, make_uint4((pack2(a[0], a[1]) & ~1u) | (ep & 1), pack2(a[2], a[3]), pack2(a[4], a[5]), pack2(a[6], a[7])));
                sts4(ts + o16 + i * 1024 + 512, make_uint4((pack2(a[8], a[9]) & ~1u) | (ep & 1), pack2(a[10], a[11]), pack2(a[12], a[13]), pack2(a[14], a[15])));
                asm volatile("fence.proxy.async.shared::cta;" ::: "memory");
                __syncwarp();
                asm volatile("{.reg .pred p; elect.sync _|p, 0xffffffff; @p cp.async.bulk.global.shared::cta.bulk_group [%0], [%1], 1024;}"
                             :: "l"(tp + blkc * 1024), "r"(ts + i * 1024) : "memory");
            };
            if (t < 2) mbar_wait(sb + MB_F + 16 + 8 * t, 0); else if (t == 2) bar_sync(BAR_WO, 384); else bar_sync(BAR_O, 384);
            wg_fence();
            static_for<0, 8>([&](auto N) {
                constexpr int i = N.value >> 2, k = N.value & 3;
                wgmma_rs32<k * 2, k != 0>(acc[i], f[12 * i + k][0], f[12 * i + k][1], f[12 * i + k][2], f[12 * i + k][3], b0);
            });
            wg_commit();
            mbar_wait(sb + MB_F + 8 * (t ^ 2), 0);
            static_for<0, 2>([&](auto I) {
                constexpr int i = I.value;
                wg_fence();
                static_for<4, 12>([&](auto K) {
                    constexpr int k = K.value;
                    wgmma_rs32<(k / 4 - 1) * 256 + (k & 3) * 2, 1>(acc[i], f[12 * i + k][0], f[12 * i + k][1], f[12 * i + k][2], f[12 * i + k][3], b1);
                });
                wg_commit();
            });
            wg_wait<1>();
            st(0, ta);
            wg_wait<0>();
            if (two) st(1, tb);
            if (t == 1) bar_arrive(BAR_X, 384);
            if (t == 3) bar_arrive(BAR_Q, 384);
            TLC(0, t == 3 ? 76 : t == 1 ? 68 : 66);
            tp += 32 * 40960; ts += 16384;
        }
        asm volatile("cp.async.bulk.commit_group;" ::: "memory");
        asm volatile("cp.async.bulk.wait_group.read 0;" ::: "memory");
    } else if (warp < 12) {
        asm volatile("setmaxnreg.dec.sync.aligned.u32 48;");
        LANE_REGS;
        const int w4 = warp & 3;
        asm volatile("barrier.cluster.wait.acquire.aligned;" ::: "memory");
        const uint32_t wv_lo = ((SB0 + OFF_WV) >> 4) | (64u << 16);
        uint32_t vm0 = 0, vm1 = 0, vn0 = 0, vn1 = 0;
        (void)lane;
        if (warp == 8) {
            const int e0 = head * DH + rank * 64;
            for (int i = PWIN; i < 5; i++) {
                mbar_wait(sb + MB_F + 8 * (i - PWIN), 0);
                expect_e(sb + MB_F + 8 * i, 32768);
                tma2d_e(sb + OFF_WV + i * 16384, &tmWq, e0, i * 128, sb + MB_F + 8 * i);
                tma2d_e(sb + OFF_WO + i * 16384, &tmWk, e0, i * 128, sb + MB_F + 8 * i);
            }
            for (int i = 0; i < 5; i++) {
                mbar_wait(sb + MB_E + 8 * i, 0);
                if (i + 5 - PWIN < 5) mbar_wait(sb + MB_F + 8 * (i + 5 - PWIN), 0);
                expect_e(sb + MB_F + 8 * i, 16384);
                tma2d_e(sb + OFF_WV + i * 16384, &tmWv, e0, i * 128, sb + MB_F + 8 * i);
            }
        }
        auto pvx = [&](int seg, const uint32_t m0, const uint32_t m1, uint32_t* o, auto sync) {
            const uint4* vq = g_vx + (blockIdx.x * 64 + seg) * 256 + w4 * 32 + ((keep(l16) - sb) >> 4);
            const uint4 u = ld_pkt(vq), v = ld_pkt(vq + 128);
            const uint32_t px_lo = ((SB0 + OFF_PX) >> 4) | (8u << 16);
            sync();
            const uint32_t b[12] = {m0, m1, 0, 0, u.x, u.y, u.z, u.w, v.x, v.y, v.z, v.w};
            uint32_t a[12], z;
            asm volatile("shr.u32 %0, %1, 8;" : "=r"(z) : "r"(seg + warp));
#pragma unroll
            for (int i = 0; i < 12; i++) asm volatile("xor.b32 %0, %1, %2;" : "=r"(a[i]) : "r"(b[i]), "r"(z));
            blk(warp);
            static_for<0, 2>([&](auto H) {
                constexpr int h = H.value;
                float acc[8] = {0, 0, 0, 0, 0, 0, 0, 0};
                wg_fence();
                wgmma_rs16<h * 80, 0>(acc, a[0], a[1], a[2], a[3], px_lo);
                wgmma_rs16<h * 80 + 8, 1>(acc, a[4], a[5], a[6], a[7], px_lo);
                if constexpr (h == 1) wgmma_rs16<h * 80 + 24, 1>(acc, a[8], a[9], a[10], a[11], px_lo);
                wg_commit();
                wg_wait<0>();
#pragma unroll
                for (int i = 0; i < 4; i++) o[4 * h + i] = keep(pack2(acc[2 * i], acc[2 * i + 1]));
                blk(warp);
            });
        };
        auto stage = [&](uint32_t dst, const uint32_t* o) {
            const uint32_t ln = (keep(l16) - sb) >> 4;
            const uint32_t sa = sb + dst + ((ln & 7) + ((ln >> 4) << 3)) * 128 + (((2 * w4 + ((ln >> 3) & 1)) ^ (ln & 7)) << 4);
            stsm4t(sa, o[0], o[1], o[2], o[3]);
            stsm4t(sa + 2048, o[4], o[5], o[6], o[7]);
            asm volatile("fence.proxy.async.shared::cta;" ::: "memory");
        };

        for (int s = 0; ; s++) {
            DBGBASE;
            if (s >= NVC && s < NSEG) { arrive_e(sb + MB_EM); arrive_e(sb + MB_EN); arrive_e(sb + MB_EA); }
            float sc[10];
#pragma unroll
            for (int j = 0; j < 10; j++) sc[j] = 0.f;
            if (s > 0) {
                uint32_t o[8];
                uint32_t w[5], xo, mo;
                asm volatile("fence.proxy.async.shared::cta;" ::: "memory");
                pvx(max(s - 2, 0), vn0, vn1, o, [&]() {
                    if (warp == 9) expect_e(sb + MB_SX, 5120);
                    if (warp == 10 && s < NSEG) mbar_wait(sb + MB_XA, s & 1);
                    const uint32_t qa_lo = ((SB0 + OFF_QX) >> 4) | (1u << 16), ka_lo = ((SB0 + OFF_K1) >> 4) | (1u << 16);
                    const uint32_t p1 = mapa(sb, (rank + 1) % 3) - sb, p2 = mapa(sb, (rank + 2) % 3) - sb;
                    const uint32_t sx = s == NSEG ? OFF_SXL : OFF_SX, lz = keep(l16);
                    xo = keep(lz + sx + w4 * 640); mo = keep(sb + w4 * 640 + ((lz - sb) >> 2) + sx + 512);
                    float d[20];
#pragma unroll
                    for (int j = 0; j < 20; j++) d[j] = 0.f;
                    blk(warp);
                    if (s < NSEG) bar_sync(BAR_WO, 384);
                    wg_fence();
                    static_for<0, 4>([&](auto K4) { wgmma_ss40<K4.value * 2, K4.value != 0>(d, qa_lo, ka_lo); });
                    wg_commit();
                    wg_wait<0>();
#pragma unroll
                    for (int j = 0; j < 5; j++) w[j] = pack2(d[4 * j], d[4 * j + 1]);
                    st_async4(p1 + xo + 2560, w[1], w[2], w[3], w[4], p1 + sb + MB_SX); st_async4(p2 + xo, w[1], w[2], w[3], w[4], p2 + sb + MB_SX);
                    st_async1(p1 + mo + 2560, w[0], p1 + sb + MB_SX);                   st_async1(p2 + mo, w[0], p2 + sb + MB_SX);
                    if (s < NSEG) bar_arrive(BAR_SX, 256);
                    TSTAMP(6);
                    blk(warp);
                });
                TSTAMP(2);
                mbar_wait(sb + MB_SX, (s - 1) & 1);
                TSTAMP(0);
                const uint4 u = lds4(xo), v = lds4(xo + 2560);
                const uint32_t um = lds1(mo), vm = lds1(mo + 2560);
                const uint32_t h[5] = {badd2(um, vm), badd2(u.x, v.x), badd2(u.y, v.y), badd2(u.z, v.z), badd2(u.w, v.w)};
#pragma unroll
                for (int j = 0; j < 5; j++) { sc[2 * j] = bf_lo(h[j]) + bf_lo(w[j]); sc[2 * j + 1] = bf_hi(h[j]) + bf_hi(w[j]); }
                blk(warp);
                bar_sync(BAR_P, 128);
                stage(OFF_OX, o);
                if (s == NSEG) bar_arrive(BAR_WO, 384);
                bar_sync(BAR_P, 128);
                if (warp == 9 && s > 1) {
                    if (s == NSEG) share_o(sb, rank, OFF_OX, 0);
                    else if (l16 == sb) {
                        tma_st(&tmOx, sb + OFF_OX, blockIdx.x * 64, (s - 2) * 32);
                        asm volatile("cp.async.bulk.commit_group;" ::: "memory");
                        if (prog_step(s)) asm volatile("cp.async.bulk.wait_group 0;" ::: "memory");
                        else asm volatile("cp.async.bulk.wait_group.read 0;" ::: "memory");
                    }
                    __syncwarp();
                }
            }
            TSTAMP(8);
            auto softmax = [&]() {
                const uint32_t lz = keep(l16), o16 = lz - sb;
                const int lim = 8 + 8 * w4 + (o16 >> 6) - ((o16 >> 3) & 6);
#pragma unroll
                for (int j = 2; j < 10; j++) if (8 * (j >> 1) + (j & 1) > lim) sc[j] = -3.0e38f;
                float mx = fmaxf(fmaxf(fmaxf(fmaxf(sc[2], sc[3]), fmaxf(sc[4], sc[5])), fmaxf(fmaxf(sc[6], sc[7]), fmaxf(sc[8], sc[9]))), fmaxf(sc[0], sc[1]));
                mx = fmaxf(mx, __shfl_xor_sync(0xffffffffu, mx, 1));
                mx = fmaxf(mx, __shfl_xor_sync(0xffffffffu, mx, 2));
                mx *= -SCL_B;
                float sum = 0.f;
#pragma unroll
                for (int j = 0; j < 10; j++) { sc[j] = ex2(fmaf(sc[j], SCL_B, mx)); sum += sc[j]; }
                sum += __shfl_xor_sync(0xffffffffu, sum, 1);
                sum += __shfl_xor_sync(0xffffffffu, sum, 2);
                const float inv = rcpf(sum);
                stsm4(lz + (OFF_PX + 128) + w4 * 640, pack2(sc[2] * inv, sc[3] * inv), pack2(sc[4] * inv, sc[5] * inv), pack2(sc[6] * inv, sc[7] * inv), pack2(sc[8] * inv, sc[9] * inv));
                sts1(sb + OFF_PX + w4 * 640 + ((lz - sb) >> 2), pack2(sc[0] * inv, sc[1] * inv));
            };
            if (s == NSEG) {
                uint32_t o[8];
                pvx(s - 1, vm0, vm1, o, [&]() {
                    softmax();
                    asm volatile("fence.proxy.async.shared::cta;" ::: "memory");
                    blk(warp);
                    bar_sync(BAR_P, 128);
                });
                stage(OFF_OXL, o);
                bar_arrive(BAR_O, 384);
                bar_sync(BAR_P, 128);
                if (warp == 9) share_o(sb, rank, OFF_OXL, 1);
                TLC(10, s);
                break;
            }
            TLC(10, s);
            bar_arrive(BAR_K, 416);
            uint4* vp = g_vx + (blockIdx.x * 64 + s) * 256 + w4 * 32 + ((keep(l16) - sb) >> 4);
            if (s < NVC) {
                const uint32_t xr_lo = ((SB0 + OFF_XR) >> 4) | (1u << 16);
                float acc[16];
#pragma unroll
                for (int i = 0; i < 16; i++) acc[i] = 0.f;
                mbar_wait(sb + MB_XA, s & 1);
                mbar_wait(sb + MB_XB, s & 1);
                static_for<0, 10>([&](auto KB) {
                    constexpr int kb = KB.value;
                    if (!(kb & 1) && s == 0) {
                        mbar_wait(sb + MB_E + 4 * kb, 0);
                        mbar_wait(sb + MB_F + 4 * kb, 1);
                        if (warp == 8) {
                            auto row = [&](uint32_t p) { return head * DH + (rank + p) % 3 * 64; };
                            auto wa = [&](uint32_t w, uint32_t p) { tma2d_e(sb + OFF_WO + w * HALF + p * 8192, &tmWo, (w * 5 + rank) * 64, row(p), sb + MB_WO); };
                            auto wb = [&](uint32_t j0, uint32_t j1) {
#pragma unroll 1
                                for (uint32_t i = 3 * j0; i < 3 * j1; i++) tma2d_e(sb + wo_b(i / 3) + i % 3 * 2048, &tmWb, tile_b(i / 3 * 3 + rank) * 16, row(i % 3), sb + MB_WO);
                            };
                            if (kb == 0) { wa(0, 0); wa(0, 1); }
                            if (kb == 2) { wa(0, 2); wb(0, 1); }
                            if (kb == 4) { wa(1, 0); wb(1, 2); }
                            if (kb == 6) { wa(1, 1); wa(1, 2); }
                            if (kb == 8) wb(2, rank ? 5 : 6);
                        }
                    }
                    wg_fence();
                    static_for<0, 4>([&](auto K4) {
                        constexpr int k4 = K4.value;
                        wgmma_ss32<(kb * 4 + k4) * 128, xblk(kb) / 16 + k4 * 2, (kb | k4) != 0>(acc, wv_lo, xr_lo);
                    });
                    wg_commit();
                });
                wg_wait<0>();
                arrive_e(sb + MB_EM); arrive_e(sb + MB_EN); arrive_e(sb + MB_EA);
                vp[0] = make_uint4(pack2(acc[0], acc[1]), pack2(acc[2], acc[3]), pack2(acc[4], acc[5]), pack2(acc[6], acc[7]));
                vp[128] = make_uint4(pack2(acc[8], acc[9]), pack2(acc[10], acc[11]), pack2(acc[12], acc[13]), pack2(acc[14], acc[15]));
            }
            softmax();
            TSTAMP(7);
            blk(warp);
            const uint4 vu = ld_pkt(vp), vv = ld_pkt(vp + 128);
            TSTAMP(1);
            {
                uint32_t pm; asm volatile("shr.u32 %0, %1, 1;" : "=r"(pm) : "r"(l16 + sb));
                const uint32_t va = pm + OFF_VM + w4 * 256;
                const uint32_t o8 = pm - sb, oo = keep(sb + OFF_Q1 + w4 * 256 + (o8 & 56) * 4 + (((o8 >> 2) ^ (o8 >> 1)) & 16));
                const uint32_t p1 = mapa(sb, (rank + 1) % 3), p2 = mapa(sb, (rank + 2) % 3), o4 = (o8 & 224) + ((o8 >> 3) & 16) + ((o8 >> 1) & 12) + w4 * 256;
                const uint32_t r1 = keep(p1 + o4 + OFF_K0), r2 = keep(p2 + o4 + OFF_Q0), r3 = keep(r1 ^ 16), r4 = keep(r2 ^ 16);
                if (warp == 11 && s < NSEG - 1) expect_e(sb + MB_O, 2048);
                bar_sync(BAR_V, 384);
                const float2 v0 = lds2f(va), v1 = lds2f(va + 1024);
                vn0 = vm0; vn1 = vm1;
                vm0 = badd2(__float_as_uint(v0.x), __float_as_uint(v1.x)); vm1 = badd2(__float_as_uint(v0.y), __float_as_uint(v1.y));
                TSTAMP(3);
                if (s == NSEG - 1) {
                    bar_sync(BAR_PM, 384);
                    if (warp == 8) {
                        asm volatile("fence.proxy.async;" ::: "memory");
                        expect_e(sb + MB_F + 16, 12288); expect_e(sb + MB_F + 24, 12288);
#pragma unroll 1
                        for (uint32_t i = 0; i < 6; i++)
                            tma2d_e(sb + OFF_OXE + i * 4096, &tmOx, (head * 3 + (rank + i) % 3) * 64, (NSEG - 4 + i / 3) * 32, sb + MB_F + 16 + i / 3 * 8);
                    }
                } else {
                const uint32_t m1 = keep(p1 + MB_O), m2 = keep(p2 + MB_O);
                blk(warp);
                bar_sync(BAR_PM, 384);
                const uint4 qq = lds4(l16 + OFF_PM + 256);
                const uint32_t q0 = lds1(pm + OFF_PM);
                float oa[4] = {0, 0, 0, 0}, ob[4] = {0, 0, 0, 0}, oc[4] = {0, 0, 0, 0};
                blk(warp);
                mma16(oa, vu.x, vu.y, vu.z, vu.w, qq.x, qq.y);
                TSTAMP(4);
                mma16(ob, vv.x, vv.y, vv.z, vv.w, qq.z, qq.w);
                mma8(oc, vm0, vm1, q0);
                blk(warp);
                const uint32_t o0 = pack2((oa[0] + ob[0]) + oc[0], (oa[1] + ob[1]) + oc[1]), o1 = pack2((oa[2] + ob[2]) + oc[2], (oa[3] + ob[3]) + oc[3]);
                st_async1(r1, o0, m1); st_async1(r2, o0, m2);
                st_async1(r3, o1, m1); st_async1(r4, o1, m2);
                stsm2(oo, o0, o1);
                bar_arrive(BAR_O, 384);
                TSTAMP(5);
                bar_arrive(BAR_X, 160);
                if (warp == 11) { mbar_wait(sb + MB_O, s & 1); bar_arrive(BAR_OR, 288); }
                if (warp == 8 && s + 1 >= NVC)
                    asm volatile("prefetch.global.L2 [%0];" :: "l"(g_vx + (blockIdx.x * 64 + s + 1) * 256 + ((keep(l16) - sb) >> 1)));
                if (warp == 9 && l16 < sb + 64 && blockIdx.x < 80 && s < NSEG - 2)
                    asm volatile("prefetch.global.L2 [%0];" :: "l"(xin + (s + 2) * 40960 + blockIdx.x * 512 + (keep(l16) - sb) * 8));
                }
            }
        }
    } else {
        asm volatile("setmaxnreg.dec.sync.aligned.u32 48;");
        LANE_REGS;
        const int g = warp & 3;
        sts1(sb + OFF_EP, ep0 + 1);
        if ((g & 1) && lane == 0) asm volatile("st.relaxed.gpu.global.b32 [%0], %1;" :: "l"(pp + (g >> 1) * 4096), "r"(0) : "memory");
        {
            uint4 v[5];
#pragma unroll
            for (int i = 0; i < 5; i++) {
                const unsigned short* m = reinterpret_cast<const unsigned short*>(mem0) + g * 160 + lane + 32 * i;
                v[i].x = m[0] | ((uint32_t)m[DM] << 16);          v[i].y = m[2 * DM] | ((uint32_t)m[3 * DM] << 16);
                v[i].z = m[4 * DM] | ((uint32_t)m[5 * DM] << 16); v[i].w = m[6 * DM] | ((uint32_t)m[7 * DM] << 16);
            }
            asm volatile("barrier.cluster.wait.acquire.aligned;" ::: "memory");
            mbar_wait_long(sb + MB_EM, 0); mbar_wait_long(sb + MB_EN, 0);
#pragma unroll
            for (int i = 0; i < 5; i++) sts4(sb + OFF_MEMT + g * 2560 + 512 * i + ((lane & 7) + ((lane >> 4) << 3)) * 32 + (((lane >> 3) ^ (lane >> 2)) & 1) * 16, v[i]);
            bar_sync(BAR_R, 128);
        }
        uint32_t hph = 0;
        const uint32_t gj = g == 3 ? 0 : g == 1 ? 10 : g == 2 ? 6 : 16, gn = g & 1 ? 3072 : 2048, gb = (0xce09u | 0xd0u) >> 4 * g & 15;
        static_assert(bar_g(1, 1) == 9 && bar_g(0, 1) == 13 && bar_g(1, 0) == 14 && bar_g(0, 0) == 12, "barriers");
        if (g == 3) bar_arrive(bar_g(0, 0), 160); else if (g == 1) bar_arrive(bar_g(0, 1), 160); else if (g == 2) bar_arrive(bar_g(1, 0), 160); else bar_arrive(bar_g(1, 1), 160);

        for (int s = 0; ; s++) {
            DBGBASE;
            uint32_t lz = l16 + lds1(sb + OFF_ZERO), o16 = lz - sb;
            mbar_wait(sb + MB_EA, s & 1);
            if (g == XG && s < NSEG - 1) {
                if (s == SW - 1 && o16 == 0) {
                    const uint32_t t0 = lds1(sb + OFF_PRB), t1 = lds1(sb + OFF_PRB + 4), nr = lds1(sb + OFF_EP) * 2 + (HOME && t1 < t0);
                    asm volatile("st.relaxed.gpu.global.v4.b32 [%0], {%1,%1,%1,%1}; st.relaxed.gpu.global.v4.b32 [%0 + 16], {%1,%1,%1,%1};"
                                 :: "l"(g_near + blockIdx.x * 8), "r"(nr) : "memory");
                }
                __syncwarp();
#ifdef NOXA
                expect_e(sb + MB_XA, 2 * 4096);
#else
                expect_e(sb + MB_XA, 9 * 4096);
                asm volatile("{.reg .pred p; elect.sync _|p, 0xffffffff;\n"
                             "@p cp.async.bulk.tensor.3d.shared::cluster.global.mbarrier::complete_tx::bytes [%0], [%1, {0, %3, 3}], [%2];}"
                             :: "r"(sb + OFF_XR), "l"(&tmX7), "r"(sb + MB_XA), "r"((s + 1) * 32) : "memory");
#endif
            }
            {
                const uint32_t ln = o16 >> 4, r7 = sb + (ln & 7) * 128;
                const uint32_t lo = keep(r7 + (((ln >> 3) ^ (ln & 7)) << 4) + OFF_K1), lo2 = keep(lo ^ 64);
                const uint32_t lq = keep(r7 + (ln & 8) * (HALF / 8) + (((ln >> 4) ^ (ln & 7)) << 4) + OFF_Q0);
                const uint32_t so = keep(OFF_SM + (ln >> 2) * 160 + (ln & 3) * 8 + (g == 1 ? 0 : g == 0 ? 32 : 96));
                const uint32_t p1 = mapa(sb, (rank + 1) % 3), p2 = mapa(sb, (rank + 2) % 3);
                auto send = [&](float x, float y, uint32_t o) {
                    st_async2(p1 + so + (OFF_SP - OFF_SM + o), __float_as_uint(x), __float_as_uint(y), p1 + MB_S);
                    st_async2(p2 + so + (OFF_SP + 1280 - OFF_SM + o), __float_as_uint(x), __float_as_uint(y), p2 + MB_S);
                    sts2(sb + so + o, __float_as_uint(x), __float_as_uint(y));
                };
                uint32_t a[4][4], b[4][4];
                auto lda = [&]() {
                    const uint32_t lq1 = keep(lq ^ 32), lq2 = keep(lq ^ 64), lq3 = keep(lq ^ 96);
                    TS2(0);
                    blk(warp);
                    bar_sync(BAR_Q, 352);
                    ldsm4(lq, a[0][0], a[0][1], a[0][2], a[0][3]);
                    ldsm4(lq1, a[1][0], a[1][1], a[1][2], a[1][3]);
                    ldsm4(lq2, a[2][0], a[2][1], a[2][2], a[2][3]);
                    ldsm4(lq3, a[3][0], a[3][1], a[3][2], a[3][3]);
                    blk(warp);
                };
                auto ldb = [&](uint32_t o, uint32_t d) {
                    ldsm4(lo + o, b[0][0], b[0][1], b[0][2], b[0][3]);
                    ldsm4(lo + o + d, b[1][0], b[1][1], b[1][2], b[1][3]);
                    ldsm4(lo2 + o, b[2][0], b[2][1], b[2][2], b[2][3]);
                    ldsm4(lo2 + o + d, b[3][0], b[3][1], b[3][2], b[3][3]);
                };
                if (g == 1) {
                    lda();
                    bar_sync(BAR_K, 416);
                    ldb(0, -HALF);
                    if (W0 && s == 0) mbar_wait_long(sb + MB_WO, 0);
                    bar_arrive(BAR_S, 288);
                    blk(warp);
                    float d0[4] = {0, 0, 0, 0}, d1[4] = {0, 0, 0, 0}, d2[4] = {0, 0, 0, 0}, d3[4] = {0, 0, 0, 0};
#pragma unroll
                    for (int i = 0; i < 4; i++) b[0][i] = badd2(b[0][i], b[1][i]);
                    mma16(d0, a[0][0], a[0][1], a[0][2], a[0][3], b[0][0], b[0][1]);
                    TS2(3);
                    mma16(d1, a[1][0], a[1][1], a[1][2], a[1][3], b[0][2], b[0][3]);
                    blk(warp);
#pragma unroll
                    for (int i = 0; i < 4; i++) b[2][i] = badd2(b[2][i], b[3][i]);
                    mma16(d2, a[2][0], a[2][1], a[2][2], a[2][3], b[2][0], b[2][1]);
                    mma16(d3, a[3][0], a[3][1], a[3][2], a[3][3], b[2][2], b[2][3]);
                    blk(warp);
                    send(((d0[0] + d0[2]) + (d1[0] + d1[2])) + ((d2[0] + d2[2]) + (d3[0] + d3[2])),
                         ((d0[1] + d0[3]) + (d1[1] + d1[3])) + ((d2[1] + d2[3]) + (d3[1] + d3[3])), 0);
                    TS2(5);
                    stsm4(lo, b[0][0], b[0][1], b[0][2], b[0][3]);
                    stsm4(lo2, b[2][0], b[2][1], b[2][2], b[2][3]);
                    expect_e(sb + MB_S, 512);
                } else if (g != 2) {
                    ldb(1024 + (g >> 1) * 2048, 1024);
                    lda();
                    float d0[4] = {0, 0, 0, 0}, d1[4] = {0, 0, 0, 0};
#pragma unroll
                    for (int k = 0; k < 4; k++) {
                        mma16(d0, a[k][0], a[k][1], a[k][2], a[k][3], b[k & 2][2 * (k & 1)], b[k & 2][2 * (k & 1) + 1]);
                        if (k == 0) TS2(1);
                        mma16(d1, a[k][0], a[k][1], a[k][2], a[k][3], b[(k & 2) + 1][2 * (k & 1)], b[(k & 2) + 1][2 * (k & 1) + 1]);
                        blk(warp);
                    }
                    send(d0[0] + d0[2], d0[1] + d0[3], 0);
                    send(d1[0] + d1[2], d1[1] + d1[3], 32);
                    TS2(2);
                    __syncwarp();
                    expect_e(sb + MB_S, 1024);
                }
                TSTAMP(7);
            }
            if (s < SW) {
            o16 = l16 + lds1(sb + OFF_ZERO) - sb;
            if (s == SW - 2 && (g & 1)) {
                if (o16 == 0) {
                    uint32_t t = ~0u;
#pragma unroll 1
                    for (int i = 0; i < NPROBE; i++) {
                        const uint32_t c0 = clk32();
                        uint32_t c1 = c0 - 1;
                        asm volatile("{.reg .pred p; .reg .b32 x; atom.relaxed.gpu.global.exch.b32 x, [%1], %2; setp.le.u32 p, x, %2; @p mov.u32 %0, %%clock;}"
                                     : "+r"(c1) : "l"(win + (0x140000 + (blockIdx.x & 63) * 64 + (blockIdx.x >> 6) * 0x4000 + (g >> 1) * 4096 + o16)), "r"(i) : "memory");
                        t = min(t, c1 - c0);
                    }
                    sts1(sb + OFF_PRB + (g >> 1) * 4, t);
                }
                __syncwarp();
            }
            if (s == SW - 1 && g == 0) {
                uint32_t a0, a1, a2;
                const uint32_t ep = lds1(sb + OFF_EP);
#pragma unroll 1
                for (int c = 0; c < SPIN_LIM; c++) {
                    a0 = ld_relaxed(g_near + o16 / 2); a1 = ld_relaxed(g_near + 256 + o16 / 2); a2 = ld_relaxed(g_near + 512 + o16 / 2);
                    if (__all_sync(0xffffffffu, ((a0 ^ ep * 2) | (a1 ^ ep * 2) | (a2 ^ ep * 2)) < 2)) break;
                    __nanosleep(100);
                }
                const uint32_t b0 = __ballot_sync(0xffffffffu, a0 & 1), b1 = __ballot_sync(0xffffffffu, a1 & 1), b2 = __ballot_sync(0xffffffffu, a2 & 1);
                const uint32_t cw = blockIdx.x >> 5, bm = cw == 0 ? b0 : cw == 1 ? b1 : b2;
                const uint32_t side = (bm >> (blockIdx.x & 31)) & 1;
                const int n1 = __popc(b0) + __popc(b1) + __popc(b2);
                const int r1 = __popc(bm & ((1u << (blockIdx.x & 31)) - 1)) + (cw > 0 ? __popc(b0) : 0) + (cw > 1 ? __popc(b1) : 0);
                const int rk = side ? r1 : blockIdx.x - r1, no = side ? 96 - n1 : n1;
                const uint32_t next = side << 8 | (rk < 40 ? 2 * rk + side : min(2 * (no + rk - 40) + (side ^ 1), 95));
                TVAL0(5, next);
                if (g == 0) { sts1(sb + OFF_KP + 4, pause_at(next & 255)); sts4(sb + OFF_RL + 16, role_tab(next & 255, side)); }
            }
            }
            lz = l16 + lds1(sb + OFF_ZERO); o16 = lz - sb;
            const uint4 rl = lds4(sb + OFF_RL + (s >= SW ? 16 : 0));
            const uint32_t tag = keep((s ^ lds1(sb + OFF_EP)) & 1), dly1 = __shfl_sync(0xffffffffu, rl.z, 0);
            const char *mb = win + __shfl_sync(0xffffffffu, rl.w + 0x100000 + (0x0213 >> 4 * g & 3) * 0x4000, 0), *rp = win + __shfl_sync(0xffffffffu, rl.x, 0);
            const char* wp = keepp(win + ((rl.y ^ ((o16 >> 3) & 16)) + g * 32 + ((o16 >> 5) & 8) + ((o16 >> 4) & 4) + ((o16 & 16) << 8)));
            const uint32_t ra = keep(sb + (o16 & 256 ? OFF_R1 : OFF_R0) + (o16 & 240) * 8 + ((o16 ^ (g * 32)) & 112) + ((o16 >> 4) & 8));
            const uint32_t ga = keep(sb + OFF_MEMT + gj * 512 + 2 * o16 + ((o16 >> 4) & 28)), gc = keep(ga + gn - 1024), gd = g == 3 ? H0 : g == 1 ? H1 : g == 2 ? H2 : H3;
            if (s < NSEG - 1) expect_e(sb + MB_G + 8 * g, gn);
            int cnt;
            if (g == 2) {
                if (s == 0) mbar_wait_long(sb + MB_WO, 0);
                uint32_t cal = keep(lz - l16) - clkv() * 9;
#pragma unroll
                for (int i = 0; i < 8; i++) cal = keep(cal + gtime() * 4);
                cal -= clkv() * 9;
                const char* wc = keepp(win + (XCH_CLK + ((o16 & 128) << 5) + ((o16 >> 2) & 28)) + head * 32);
                const char* cp = keepp(mb + (XCH_CLK - 0x108000 + 2 * o16));
                mbar_wait(sb + MB_S, s & 1);
                bar_arrive(BAR_SR, 288);
                if (s == NSEG - 1) break;
                const uint32_t c0 = clkv(), t0 = ((cal + c0 * 18) & ~31u) | ((s + 1) & 31);
                if (o16 < 256 && rank == 0) st_pkt4(wc, t0);
                gatev(c0 + DLYN);
                int late;
#pragma unroll 1
                for (cnt = 64; ; cnt--) {
                    late = ld_relaxed(cp) - t0;
                    if (!__any_sync(0xffffffffu, late & 31) || cnt == 0) break;
                }
                late = min(__reduce_max_sync(0xffffffffu, late), 64000);
                sts1(sb + OFF_TG, c0 + (late * 57 >> 10));
                TVAL(4, 64 - cnt);
            } else {
                if (g == 1 && s < NSEG - 1) {
                    gatev(clkv() + HS);
                    asm volatile("fence.proxy.async.shared::cta;" ::: "memory");
                    tma2d_e(sb + OFF_MEMT, &tmX, 0, (s + 1) * 32, sb + MB_XA);
                    tma2d_e(sb + OFF_MEMT + 4096, &tmX, 64, (s + 1) * 32, sb + MB_XA);
                }
                if (g == 1 && prog_step(s) && o16 == 0) st_release(g_prog + blockIdx.x, lds1(sb + OFF_EP) * 128 + s - 1);
                __syncwarp();
                if (s == NSEG - 1) break;
#ifndef PROF
                if (g == 0 && (((s & 7) == 6 && s < NSEG - 2) || s == NVC - 2)) {
                    const uint32_t* fv = g_flagv + blockIdx.x * 64 + s + 2;
                    const uint32_t e = lds1(sb + OFF_EP);
                    for (int c = 0; c < SPIN_LIM && ld_acquire(fv) != e; c++) { }
                }
#endif
                if (g == 1) {
                    bar_sync(BAR_X, 160);
                    asm volatile("fence.proxy.async.shared::cta;" ::: "memory");
                    expect_e(sb + MB_XB, 4096);
                    tma2d_e(sb + OFF_MEMT + 8192, &tmX, 128, (s + 1) * 32, sb + MB_XB);
                } else if (g == 3) {
                    if (dly1) expect_e(sb + MB_H, 4096);
                    bar_sync(BAR_OF, 288);
                    sts1(sb + OFF_SP + (o16 >> 2), 0x3f803f80);
                    asm volatile("fence.proxy.async.shared::cta;" ::: "memory");
                }
            }
            bar_sync(BAR_R, 128);
            const uint32_t tg = lds1(sb + OFF_TG);
            TS3(0);
            auto fetch = [&]() {
                asm volatile("{.reg .pred p; elect.sync _|p, 0xffffffff;\n"
                             "@p cp.async.bulk.shared::cluster.global.mbarrier::complete_tx::bytes [%0], [%1], %2, [%3];}"
                             :: "r"(sb + OFF_MEMT + gj * 512), "l"(mb), "r"(gn), "r"(sb + MB_G + 8 * g) : "memory");
            };
            if (dly1) {
                const uint32_t d_lo = SB0 >> 4;
                if (g == 3) {
                    gatev(tg + dly1);
                    asm volatile("{.reg .pred p; elect.sync _|p, 0xffffffff;\n"
                                 "@p cp.async.bulk.shared::cluster.global.mbarrier::complete_tx::bytes [%0], [%2], 2048, [%4];\n"
                                 "@p cp.async.bulk.shared::cluster.global.mbarrier::complete_tx::bytes [%1], [%3], 2048, [%4];}"
                                 :: "r"(sb + OFF_R0), "r"(sb + OFF_R1), "l"(rp), "l"(rp + 2048), "r"(sb + MB_H) : "memory");
                }
                TS3(1);
                mbar_wait_long(sb + MB_H, hph);
                const uint32_t tw = lds1(ra);
                float d[4] = {0, 0, 0, 0};
                wg_fence();
                wgmma_ss8<OFF_R0 / 16, OFF_SP / 16, 0>(d, d_lo | (64u << 16), d_lo);
                wgmma_ss8<OFF_R1 / 16, OFF_SP / 16, 1>(d, d_lo | (64u << 16), d_lo);
                wg_commit();
                sched();
                uint32_t tv; asm volatile("{.reg .pred p; setp.ne.u32 p, %1, 0; vote.sync.ballot.b32 %0, p, 0xffffffff;}" : "=r"(tv) : "r"(tag) : "memory");
                const bool stale = any_bit0(tw ^ tv, 0);
                wg_wait<0>();
                auto word = [&](float lo, float hi) {
                    const uint32_t tr = __float_as_uint(lo) >> 16;
                    return __byte_perm(tr + ((tr ^ tag) & 1), pack2(0.f, hi), 0x7610);
                };
                const uint32_t pk = word(d[0], d[2]);
                if (!stale) st_pkt4(wp, pk);
                hph ^= 1;
                TS3(2);
                cnt = 4 * WAIT_LIM;
                if (__builtin_expect(stale, 0)) {
                    const uint32_t o = (ga >> 1) & 496;
                    const char* p = rp + (o * 8 + (ra & 112));
                    uint4 u, v;
#pragma unroll 1
                    do { u = ld_pkt(p); v = ld_pkt(p + (16 - 2 * (int)(ra & 16))); } while (any_bit0(tagx(u.x, u.z, tag), tagx(v.x, v.z, tag)) && --cnt);
                    const uint32_t w[8] = {u.x, u.y, u.z, u.w, v.x, v.y, v.z, v.w};
                    float r[16];
#pragma unroll
                    for (int i = 0; i < 16; i++) r[i] = i & 2 ? bf_hi(w[(i & 1) * 4 + (i >> 2)]) : bf_lo(w[(i & 1) * 4 + (i >> 2)]);
                    static_for<0, 3>([&](auto K) {
                        constexpr int k = 8 >> K.value;
                        const bool up = o & (32 * k);
#pragma unroll
                        for (int i = 0; i < k; i++) {
                            const float a = r[i], b = r[k + i];
                            r[i] = __uint_as_float(selu(up, __float_as_uint(b), __float_as_uint(a))) + __shfl_xor_sync(0xffffffffu, __uint_as_float(selu(up, __float_as_uint(a), __float_as_uint(b))), 2 * k);
                        }
                    });
#pragma unroll
                    for (int k = 2; k; k >>= 1) { r[0] += __shfl_xor_sync(0xffffffffu, r[0], k); r[1] += __shfl_xor_sync(0xffffffffu, r[1], k); }
                    st_pkt4(wp, word(r[0], r[1]));
                    cnt--;
                }
                TVAL(8, 4 * WAIT_LIM - cnt);
            }
#ifdef PRB
            if (!dly1 && s == g_s0 && g == PRB) {
                uint32_t z = 0, t = 0;
                uint32_t ln = (ga >> 5) & 31;
#pragma unroll
                for (int i = 0; i < 32; i++) {
#if PRK == 0
                    z = lds1(sb + OFF_ZERO + z);
#elif PRK == 1
                    z = __shfl_xor_sync(0xffffffffu, z, 1);
#else
                    for (int k = 0; k < 8; k++) asm volatile("lop3.b32 %0, %0, %1, %1, 0x80;" : "+r"(z) : "r"(ln));
#endif
                    asm volatile("{.reg .pred p; .reg .b32 u; add.u32 u, %1, %3; setp.eq.u32 p, u, %2; @p mov.u32 %0, %%clock;}" : "+r"(t) : "r"(z), "r"(ln), "n"(0) , "r"(0));
                    asm volatile("" ::: "memory");
                    ln -= 1;
                }
                g_dbg[blockIdx.x * 512 + 256 + ((ga >> 5) & 31)] = t;
            }
#endif
            mbar_wait(sb + (g ? MB_EM : MB_EN), (s + 1) & 1);
            TS3(3);
            gatev(tg + gd);
            TS3(5);
            fetch();
#pragma unroll 1
            for (cnt = 4 * WAIT_LIM; ; cnt--) {
                mbar_wait(sb + MB_G + 8 * g, s & 1);
                const uint32_t q0 = lds1(ga), q1 = lds1(ga + 1024), q2 = lds1(gc), b0 = tagx(q0, q1, tag), b1 = q2 ^ tag;
                if (!stale_or_arrive<160>(b0, b1, gb)) break;
                if (cnt == 0) { bar_arrive(gb, 160); break; }
                arrive_e(sb + MB_G + 8 * g);
                expect_e(sb + MB_G + 8 * g, gn);
                fetch();
            }
            TSTAMP(6);
            TVAL(9, 4 * WAIT_LIM - cnt);
        }
        uint32_t u, c, sb2, rk;
        asm volatile("mov.u32 %0, %%tid.x; mov.u32 %1, %%ctaid.x; mov.u32 %2, %%dynamic_smem_size; mov.u32 %3, %%cluster_ctarank;"
                     : "=r"(u), "=r"(c), "=r"(sb2), "=r"(rk));
        sb2 += sb - CHAIN_SMEM; rk %= 3;
        const uint32_t g2 = __shfl_sync(0xffffffffu, (u >> 5) & 3, 0), ln = u & 31;
        if (g2 == 1) {
            expect_e(sb2 + MB_F, 8192); expect_e(sb2 + MB_F + 8, 8192);
        }
        asm volatile("setmaxnreg.inc.sync.aligned.u32 96;");
        const uint32_t et = ld_epoch();
        const uint4* rp = g_tail + g2 * 8 * 2560 + c * 32 + ln;
        bf16* op = out + (size_t)((NSEG - 4) * 32 + (c & 1) * 16 + (g2 >> 1) * 8 + (ln >> 2)) * OUTW + DM + (c >> 1) * 16 + (g2 & 1) * 8 + (ln & 3) * 2;
#pragma unroll 1
        for (int t = 0; t < 4; t++) {
            if (t == 0) bar_sync(BAR_X, 384);
            if (t == TX0) bar_sync(BAR_Q, 384);
            if (c >= 80) continue;
            uint4 q[8];
#pragma unroll
            for (int i = 0; i < 8; i++) q[i] = ld_pkt(rp + 2560 * i);
            for (int cnt = 4 * WAIT_LIM; cnt; cnt--) {
                uint32_t bad = 0;
#pragma unroll
                for (int i = 0; i < 8; i++) bad |= q[i].x ^ et;
                if (!any_bit0(bad, bad)) break;
                static_for<0, 8>([&](auto I) { ld_pkt_stale<I.value * 40960>(q[I.value], rp, et); });
            }
            TLC(12, t == 3 ? 78 : t == 2 ? 79 : 77);
            float r[8] = {0, 0, 0, 0, 0, 0, 0, 0};
#pragma unroll
            for (int i = 0; i < 8; i++) {
                r[0] += bf_lo(q[i].x); r[1] += bf_hi(q[i].x); r[2] += bf_lo(q[i].y); r[3] += bf_hi(q[i].y);
                r[4] += bf_lo(q[i].z); r[5] += bf_hi(q[i].z); r[6] += bf_lo(q[i].w); r[7] += bf_hi(q[i].w);
            }
            const uint32_t ra = sb2 + OFF_TRED + t * 4096 + ln * 8, rb2 = ra + g2 * 1024;
#pragma unroll
            for (int j = 0; j < 4; j++) sts2(ra + j * 1024 + g2 * 256, __float_as_uint(r[2 * j]), __float_as_uint(r[2 * j + 1]));
            bar_sync(BAR_R, 128);
            const float2 x0 = lds2f(rb2), x1 = lds2f(rb2 + 256), x2 = lds2f(rb2 + 512), x3 = lds2f(rb2 + 768);
            stg1(op, movm(pack2((x0.x + x1.x) + (x2.x + x3.x), (x0.y + x1.y) + (x2.y + x3.y))));
            rp += 32 * 2560;
            op += 32 * OUTW;
        }
        TLC(12, 75);
    }
    asm volatile("barrier.cluster.arrive.release.aligned;" ::: "memory");
    asm volatile("barrier.cluster.wait.acquire.aligned;" ::: "memory");
#if defined(DEV) || defined(TL)
    {
        uint32_t u, c, b;
        asm volatile("mov.u32 %0, %%tid.x; mov.u32 %1, %%ctaid.x; mov.u32 %2, %%dynamic_smem_size;" : "=r"(u), "=r"(c), "=r"(b));
        b += sb - CHAIN_SMEM + OFF_DBG;
#ifdef DEV
        if (u < 160) g_dbg[c * 512 + u] = lds1(b + u * 4);
#else
        if (u < 80) { g_tl[c * 80 + u] = lds1(b + u * 8); g_tc[c * 80 + u] = lds1(b + u * 8 + 4); }
#endif
    }
#endif
}

constexpr int NSIDE = 36, SST = 3, MAXJ = 32, NKS = 7;
constexpr uint32_t S_STAGE = 49152, S_STG = SST * S_STAGE, S_BAR = S_STG + 65536, SIDE_SMEM = S_BAR + 256;
constexpr uint32_t SB_FULL = S_BAR, SB_EMPTY = S_BAR + 64, SB_STAGED = S_BAR + 32, SB_FREE = S_BAR + 48;
enum { JV = 0, JQ = 1, JP = 2, JO = 3, JR = 4, JEND = 5 };
struct SideParams {
    CUtensorMap a[4], b[4], c[4], st[2], sto;
};
struct Job { uint32_t x, y; };
struct JobTable { Job j[NSIDE][MAXJ]; };
static_assert(OFF_OX % 1024 == 0 && OFF_QX % 1024 == 0 && OFF_MEMT % 1024 == 0, "swizzled tiles");
__constant__ const JobTable c_jobs = {{
    {{0x8020, 0xa0010}, {0x9220, 0xa0010}, {0x10a40, 0xa0010}, {0x641, 0xa0010}, {0x301c1, 0xa0010}, {0x204c0, 0xa0010}, {0x216c0, 0xa0010}, {0x606c1, 0xa0010}, {0x304c0, 0xa0010}, {0x31240, 0xa0010}, {0x40440, 0xa0010}, {0x30042, 0xa0010}, {0x503c0, 0xa0010}, {0x40042, 0xa0010}, {0x51640, 0xa0010}, {0x60640, 0xa0010}, {0x60042, 0xa0010}, {0x700c0, 0xa0010}, {0x70042, 0xa0010}, {0x40043, 0x200430}, {0x40044, 0x200430}, {0x60023, 0x200630}, {0x6e80a3, 0xe0771}, {0x60024, 0x200630}, {0x6e80a4, 0xe0771}, {0x70023, 0xd0870}, {0x70024, 0xd0870}, {0x5, 0x0}},
    {{0x80a0, 0xa0010}, {0x92a0, 0xa0010}, {0x10ac0, 0xa0010}, {0x6c1, 0xa0010}, {0x30241, 0xa0010}, {0x20540, 0xa0010}, {0x21740, 0xa0010}, {0x60741, 0xa0010}, {0x30540, 0xa0010}, {0x312c0, 0xa0010}, {0x404c0, 0xa0010}, {0x300c2, 0xa0010}, {0x50440, 0xa0010}, {0x400c2, 0xa0010}, {0x516c0, 0xa0010}, {0x606c0, 0xa0010}, {0x600c2, 0xa0010}, {0x70140, 0xa0010}, {0x700c2, 0xa0010}, {0x400c3, 0x200430}, {0x400c4, 0x200430}, {0x600a3, 0x200630}, {0x6e8123, 0xe0771}, {0x600a4, 0x200630}, {0x6e8124, 0xe0771}, {0x700a3, 0xd0870}, {0x700a4, 0xd0870}, {0x5, 0x0}},
    {{0x8120, 0xa0010}, {0x9320, 0xa0010}, {0x10b40, 0xa0010}, {0x741, 0xa0010}, {0x302c1, 0xa0010}, {0x205c0, 0xa0010}, {0x217c0, 0xa0010}, {0x70041, 0xa0010}, {0x305c0, 0xa0010}, {0x31340, 0xa0010}, {0x40540, 0xa0010}, {0x30142, 0xa0010}, {0x504c0, 0xa0010}, {0x40142, 0xa0010}, {0x51740, 0xa0010}, {0x60740, 0xa0010}, {0x60142, 0xa0010}, {0x701c0, 0xa0010}, {0x70142, 0xa0010}, {0x40143, 0x200430}, {0x40144, 0x200430}, {0x60123, 0x200630}, {0x6e81a3, 0xe0771}, {0x60124, 0x200630}, {0x6e81a4, 0xe0771}, {0x70123, 0xd0870}, {0x70124, 0xd0870}, {0x5, 0x0}},
    {{0x81a0, 0xa0010}, {0x93a0, 0xa0010}, {0x10bc0, 0xa0010}, {0x10041, 0xa0010}, {0x30341, 0xa0010}, {0x20640, 0xa0010}, {0x43, 0x600010}, {0x609c0, 0xa0010}, {0x611c0, 0xa0010}, {0x70440, 0xa0010}, {0x70c40, 0xa0010}, {0x1040143, 0x200431}, {0x1040144, 0x200431}, {0x601a3, 0x200630}, {0x6e8223, 0xe0771}, {0x601a4, 0x200630}, {0x6e8224, 0xe0771}, {0x701a3, 0xd0870}, {0x701a4, 0xd0870}, {0x5, 0x0}},
    {{0x8220, 0xa0010}, {0x9420, 0xa0010}, {0x10c40, 0xa0010}, {0x100c1, 0xa0010}, {0x303c1, 0xa0010}, {0x206c0, 0xa0010}, {0xc3, 0x600010}, {0x60a40, 0xa0010}, {0x61240, 0xa0010}, {0x704c0, 0xa0010}, {0x70cc0, 0xa0010}, {0x10401c3, 0x200431}, {0x10401c4, 0x200431}, {0x60223, 0x200630}, {0xde8023, 0xe0772}, {0x60224, 0x200630}, {0xde8024, 0xe0772}, {0x70223, 0xd0870}, {0x70224, 0xd0870}, {0x5, 0x0}},
    {{0x82a0, 0xa0010}, {0x94a0, 0xa0010}, {0x10cc0, 0xa0010}, {0x10141, 0xa0010}, {0x30441, 0xa0010}, {0x20740, 0xa0010}, {0x143, 0x600010}, {0x60ac0, 0xa0010}, {0x612c0, 0xa0010}, {0x70540, 0xa0010}, {0x70d40, 0xa0010}, {0x1040243, 0x200431}, {0x1040244, 0x200431}, {0x1060023, 0x200631}, {0xde80a3, 0xe0772}, {0x1060024, 0x200631}, {0xde80a4, 0xe0772}, {0x6f0023, 0xe0871}, {0x6f0024, 0xe0871}, {0x5, 0x0}},
    {{0x8320, 0xa0010}, {0x9520, 0xa0010}, {0x10d40, 0xa0010}, {0x101c1, 0xa0010}, {0x304c1, 0xa0010}, {0x207c0, 0xa0010}, {0x1c3, 0x600010}, {0x60b40, 0xa0010}, {0x61340, 0xa0010}, {0x705c0, 0xa0010}, {0x70dc0, 0xa0010}, {0x2040043, 0x200432}, {0x2040044, 0x200432}, {0x10600a3, 0x200631}, {0xde8123, 0xe0772}, {0x10600a4, 0x200631}, {0xde8124, 0xe0772}, {0x6f00a3, 0xe0871}, {0x6f00a4, 0xe0871}, {0x5, 0x0}},
    {{0x83a0, 0xa0010}, {0x95a0, 0xa0010}, {0x10dc0, 0xa0010}, {0x10241, 0xa0010}, {0x30541, 0xa0010}, {0x20840, 0xa0010}, {0x243, 0x600010}, {0x60bc0, 0xa0010}, {0x613c0, 0xa0010}, {0x70640, 0xa0010}, {0x70e40, 0xa0010}, {0x20400c3, 0x200432}, {0x20400c4, 0x200432}, {0x1060123, 0x200631}, {0xde81a3, 0xe0772}, {0x1060124, 0x200631}, {0xde81a4, 0xe0772}, {0x6f0123, 0xe0871}, {0x6f0124, 0xe0871}, {0x5, 0x0}},
    {{0x8420, 0xa0010}, {0x9620, 0xa0010}, {0x10e40, 0xa0010}, {0x102c1, 0xa0010}, {0x305c1, 0xa0010}, {0x208c0, 0xa0010}, {0x50041, 0xa0010}, {0x700c1, 0xa0010}, {0x30640, 0xa0010}, {0x313c0, 0xa0010}, {0x405c0, 0xa0010}, {0x301c2, 0xa0010}, {0x50540, 0xa0010}, {0x401c2, 0xa0010}, {0x517c0, 0xa0010}, {0x607c0, 0xa0010}, {0x601c2, 0xa0010}, {0x70240, 0xa0010}, {0x701c2, 0xa0010}, {0x401c3, 0x200430}, {0x401c4, 0x200430}, {0x10601a3, 0x200631}, {0xde8223, 0xe0772}, {0x10601a4, 0x200631}, {0xde8224, 0xe0772}, {0x6f01a3, 0xe0871}, {0x6f01a4, 0xe0871}, {0x5, 0x0}},
    {{0x84a0, 0xa0010}, {0x96a0, 0xa0010}, {0x10ec0, 0xa0010}, {0x10341, 0xa0010}, {0x30641, 0xa0010}, {0x20940, 0xa0010}, {0x500c1, 0xa0010}, {0x70141, 0xa0010}, {0x306c0, 0xa0010}, {0x31440, 0xa0010}, {0x40640, 0xa0010}, {0x30242, 0xa0010}, {0x505c0, 0xa0010}, {0x40242, 0xa0010}, {0x60040, 0xa0010}, {0x60840, 0xa0010}, {0x60242, 0xa0010}, {0x702c0, 0xa0010}, {0x70242, 0xa0010}, {0x40243, 0x200430}, {0x40244, 0x200430}, {0x1060223, 0x200631}, {0x14e8023, 0xd0773}, {0x1060224, 0x200631}, {0x14e8024, 0xd0773}, {0x6f0223, 0xe0871}, {0x6f0224, 0xe0871}, {0x5, 0x0}},
    {{0x8520, 0xa0010}, {0x9720, 0xa0010}, {0x10f40, 0xa0010}, {0x103c1, 0xa0010}, {0x306c1, 0xa0010}, {0x209c0, 0xa0010}, {0x50141, 0xa0010}, {0x701c1, 0xa0010}, {0x30740, 0xa0010}, {0x314c0, 0xa0010}, {0x406c0, 0xa0010}, {0x41140, 0xa0010}, {0x50640, 0xa0010}, {0x50e40, 0xa0010}, {0x600c0, 0xa0010}, {0x608c0, 0xa0010}, {0x610c0, 0xa0010}, {0x70340, 0xa0010}, {0x70b40, 0xa0010}, {0x1040043, 0x200431}, {0x1040044, 0x200431}, {0x2060023, 0x200632}, {0x14e80a3, 0xd0773}, {0x2060024, 0x200632}, {0x14e80a4, 0xd0773}, {0xdf0023, 0xe0872}, {0xdf0024, 0xe0872}, {0x5, 0x0}},
    {{0x85a0, 0xa0010}, {0x97a0, 0xa0010}, {0x10fc0, 0xa0010}, {0x10441, 0xa0010}, {0x30741, 0xa0010}, {0x20a40, 0xa0010}, {0x501c1, 0xa0010}, {0x70241, 0xa0010}, {0x307c0, 0xa0010}, {0x31540, 0xa0010}, {0x40740, 0xa0010}, {0x411c0, 0xa0010}, {0x506c0, 0xa0010}, {0x50ec0, 0xa0010}, {0x60140, 0xa0010}, {0x60940, 0xa0010}, {0x61140, 0xa0010}, {0x703c0, 0xa0010}, {0x70bc0, 0xa0010}, {0x10400c3, 0x200431}, {0x10400c4, 0x200431}, {0x20600a3, 0x200632}, {0x14e8123, 0xd0773}, {0x20600a4, 0x200632}, {0x14e8124, 0xd0773}, {0xdf00a3, 0xe0872}, {0xdf00a4, 0xe0872}, {0x5, 0x0}},
    {{0x8620, 0xa0010}, {0x10040, 0xa0010}, {0x11040, 0xa0010}, {0x104c1, 0xa0010}, {0x20040, 0xa0010}, {0x20ac0, 0xa0010}, {0x50241, 0xa0010}, {0x30040, 0xa0010}, {0x30840, 0xa0010}, {0x315c0, 0xa0010}, {0x407c0, 0xa0010}, {0x41240, 0xa0010}, {0x20043, 0x600210}, {0x50043, 0x200530}, {0x50044, 0x200530}, {0x1b680a3, 0xe0774}, {0x1b680a4, 0xe0774}, {0xdf0123, 0xe0872}, {0xdf0124, 0xe0872}, {0x5, 0x0}},
    {{0x86a0, 0xa0010}, {0x100c0, 0xa0010}, {0x110c0, 0xa0010}, {0x10541, 0xa0010}, {0x200c0, 0xa0010}, {0x20b40, 0xa0010}, {0x502c1, 0xa0010}, {0x300c0, 0xa0010}, {0x308c0, 0xa0010}, {0x31640, 0xa0010}, {0x40840, 0xa0010}, {0x412c0, 0xa0010}, {0x200c3, 0x600210}, {0x500c3, 0x200530}, {0x500c4, 0x200530}, {0x1b68123, 0xe0774}, {0x1b68124, 0xe0774}, {0xdf01a3, 0xe0872}, {0xdf01a4, 0xe0872}, {0x5, 0x0}},
    {{0x8720, 0xa0010}, {0x10140, 0xa0010}, {0x11140, 0xa0010}, {0x105c1, 0xa0010}, {0x20140, 0xa0010}, {0x20bc0, 0xa0010}, {0x50341, 0xa0010}, {0x30140, 0xa0010}, {0x30940, 0xa0010}, {0x316c0, 0xa0010}, {0x408c0, 0xa0010}, {0x41340, 0xa0010}, {0x20143, 0x600210}, {0x50143, 0x200530}, {0x50144, 0x200530}, {0x1b681a3, 0xe0774}, {0x1b681a4, 0xe0774}, {0xdf0223, 0xe0872}, {0xdf0224, 0xe0872}, {0x5, 0x0}},
    {{0x87a0, 0xa0010}, {0x101c0, 0xa0010}, {0x111c0, 0xa0010}, {0x10641, 0xa0010}, {0x201c0, 0xa0010}, {0x20c40, 0xa0010}, {0x503c1, 0xa0010}, {0x301c0, 0xa0010}, {0x309c0, 0xa0010}, {0x31740, 0xa0010}, {0x40940, 0xa0010}, {0x413c0, 0xa0010}, {0x201c3, 0x600210}, {0x501c3, 0x200530}, {0x501c4, 0x200530}, {0x1b68223, 0xe0774}, {0x1b68224, 0xe0774}, {0x14f0023, 0xd0873}, {0x14f0024, 0xd0873}, {0x5, 0x0}},
    {{0x8820, 0xa0010}, {0x10240, 0xa0010}, {0x11240, 0xa0010}, {0x106c1, 0xa0010}, {0x20240, 0xa0010}, {0x20cc0, 0xa0010}, {0x50441, 0xa0010}, {0x30240, 0xa0010}, {0x30a40, 0xa0010}, {0x317c0, 0xa0010}, {0x409c0, 0xa0010}, {0x41440, 0xa0010}, {0x20243, 0x600210}, {0x50243, 0x200530}, {0x50244, 0x200530}, {0x2268023, 0xe0775}, {0x2268024, 0xe0775}, {0x14f00a3, 0xd0873}, {0x14f00a4, 0xd0873}, {0x5, 0x0}},
    {{0x88a0, 0xa0010}, {0x102c0, 0xa0010}, {0x112c0, 0xa0010}, {0x10741, 0xa0010}, {0x202c0, 0xa0010}, {0x20d40, 0xa0010}, {0x504c1, 0xa0010}, {0x702c1, 0xa0010}, {0x30ac0, 0xa0010}, {0x10043, 0x600110}, {0x71340, 0xa0010}, {0x1050043, 0x200531}, {0x1050044, 0x200531}, {0x22680a3, 0xe0775}, {0x22680a4, 0xe0775}, {0x14f0123, 0xd0873}, {0x14f0124, 0xd0873}, {0x5, 0x0}},
    {{0x8920, 0xa0010}, {0x10340, 0xa0010}, {0x11340, 0xa0010}, {0x20041, 0xa0010}, {0x20340, 0xa0010}, {0x20dc0, 0xa0010}, {0x50541, 0xa0010}, {0x70341, 0xa0010}, {0x30b40, 0xa0010}, {0x100c3, 0x600110}, {0x713c0, 0xa0010}, {0x10500c3, 0x200531}, {0x10500c4, 0x200531}, {0x2268123, 0xe0775}, {0x2268124, 0xe0775}, {0x14f01a3, 0xd0873}, {0x14f01a4, 0xd0873}, {0x5, 0x0}},
    {{0x89a0, 0xa0010}, {0x103c0, 0xa0010}, {0x113c0, 0xa0010}, {0x200c1, 0xa0010}, {0x203c0, 0xa0010}, {0x20e40, 0xa0010}, {0x505c1, 0xa0010}, {0x703c1, 0xa0010}, {0x30bc0, 0xa0010}, {0x10143, 0x600110}, {0x71440, 0xa0010}, {0x1050143, 0x200531}, {0x1050144, 0x200531}, {0x22681a3, 0xe0775}, {0x22681a4, 0xe0775}, {0x14f0223, 0xd0873}, {0x14f0224, 0xd0873}, {0x5, 0x0}},
    {{0x8a20, 0xa0010}, {0x10440, 0xa0010}, {0x11440, 0xa0010}, {0x20141, 0xa0010}, {0x20440, 0xa0010}, {0x20ec0, 0xa0010}, {0x50641, 0xa0010}, {0x70441, 0xa0010}, {0x30c40, 0xa0010}, {0x101c3, 0x600110}, {0x714c0, 0xa0010}, {0x10501c3, 0x200531}, {0x10501c4, 0x200531}, {0x2268223, 0xe0775}, {0x2268224, 0xe0775}, {0x1b70023, 0xe0874}, {0x1b70024, 0xe0874}, {0x5, 0x0}},
    {{0x8aa0, 0xa0010}, {0x104c0, 0xa0010}, {0x114c0, 0xa0010}, {0x201c1, 0xa0010}, {0x40041, 0xa0010}, {0x20f40, 0xa0010}, {0x506c1, 0xa0010}, {0x704c1, 0xa0010}, {0x30cc0, 0xa0010}, {0x10243, 0x600110}, {0x71540, 0xa0010}, {0x1050243, 0x200531}, {0x1050244, 0x200531}, {0x2968023, 0xe0776}, {0x2968024, 0xe0776}, {0x1b700a3, 0xe0874}, {0x1b700a4, 0xe0874}, {0x5, 0x0}},
    {{0x8b20, 0xa0010}, {0x10540, 0xa0010}, {0x11540, 0xa0010}, {0x20241, 0xa0010}, {0x400c1, 0xa0010}, {0x20fc0, 0xa0010}, {0x50741, 0xa0010}, {0x70541, 0xa0010}, {0x30d40, 0xa0010}, {0x10242, 0xa0010}, {0x40a40, 0xa0010}, {0x414c0, 0xa0010}, {0x50740, 0xa0010}, {0x50f40, 0xa0010}, {0x50042, 0xa0010}, {0x30043, 0x600310}, {0x68023, 0xd0770}, {0x68024, 0xd0770}, {0x1b70123, 0xe0874}, {0x1b70124, 0xe0874}, {0x5, 0x0}},
    {{0x8ba0, 0xa0010}, {0x105c0, 0xa0010}, {0x115c0, 0xa0010}, {0x202c1, 0xa0010}, {0x40141, 0xa0010}, {0x21040, 0xa0010}, {0x60041, 0xa0010}, {0x705c1, 0xa0010}, {0x30dc0, 0xa0010}, {0x20042, 0xa0010}, {0x40ac0, 0xa0010}, {0x41540, 0xa0010}, {0x507c0, 0xa0010}, {0x50fc0, 0xa0010}, {0x500c2, 0xa0010}, {0x300c3, 0x600310}, {0x680a3, 0xd0770}, {0x680a4, 0xd0770}, {0x1b701a3, 0xe0874}, {0x1b701a4, 0xe0874}, {0x5, 0x0}},
    {{0x8c20, 0xa0010}, {0x10640, 0xa0010}, {0x11640, 0xa0010}, {0x20341, 0xa0010}, {0x401c1, 0xa0010}, {0x210c0, 0xa0010}, {0x600c1, 0xa0010}, {0x70641, 0xa0010}, {0x30e40, 0xa0010}, {0x200c2, 0xa0010}, {0x40b40, 0xa0010}, {0x415c0, 0xa0010}, {0x50840, 0xa0010}, {0x51040, 0xa0010}, {0x50142, 0xa0010}, {0x30143, 0x600310}, {0x68123, 0xd0770}, {0x68124, 0xd0770}, {0x1b70223, 0xe0874}, {0x1b70224, 0xe0874}, {0x5, 0x0}},
    {{0x8ca0, 0xa0010}, {0x106c0, 0xa0010}, {0x116c0, 0xa0010}, {0x203c1, 0xa0010}, {0x40241, 0xa0010}, {0x21140, 0xa0010}, {0x60141, 0xa0010}, {0x706c1, 0xa0010}, {0x30ec0, 0xa0010}, {0x20142, 0xa0010}, {0x40bc0, 0xa0010}, {0x41640, 0xa0010}, {0x508c0, 0xa0010}, {0x510c0, 0xa0010}, {0x501c2, 0xa0010}, {0x301c3, 0x600310}, {0x681a3, 0xd0770}, {0x681a4, 0xd0770}, {0x2270023, 0xe0875}, {0x2270024, 0xe0875}, {0x5, 0x0}},
    {{0x8d20, 0xa0010}, {0x10740, 0xa0010}, {0x11740, 0xa0010}, {0x20441, 0xa0010}, {0x402c1, 0xa0010}, {0x211c0, 0xa0010}, {0x601c1, 0xa0010}, {0x70741, 0xa0010}, {0x30f40, 0xa0010}, {0x201c2, 0xa0010}, {0x40c40, 0xa0010}, {0x416c0, 0xa0010}, {0x50940, 0xa0010}, {0x51140, 0xa0010}, {0x50242, 0xa0010}, {0x30243, 0x600310}, {0x68223, 0xd0770}, {0x68224, 0xd0770}, {0x22700a3, 0xe0875}, {0x22700a4, 0xe0875}, {0x5, 0x0}},
    {{0x8da0, 0xa0010}, {0x107c0, 0xa0010}, {0x117c0, 0xa0010}, {0x204c1, 0xa0010}, {0x40341, 0xa0010}, {0x21240, 0xa0010}, {0x60241, 0xa0010}, {0x42, 0xa0010}, {0x30fc0, 0xa0010}, {0x20242, 0xa0010}, {0x40cc0, 0xa0010}, {0x41740, 0xa0010}, {0x509c0, 0xa0010}, {0x511c0, 0xa0010}, {0x601c0, 0xa0010}, {0x60c40, 0xa0010}, {0x61440, 0xa0010}, {0x706c0, 0xa0010}, {0x70ec0, 0xa0010}, {0x2040143, 0x200432}, {0x2040144, 0x200432}, {0x2060123, 0x200632}, {0x14e81a3, 0xd0773}, {0x2060124, 0x200632}, {0x14e81a4, 0xd0773}, {0x2270123, 0xe0875}, {0x2270124, 0xe0875}, {0x5, 0x0}},
    {{0x8e20, 0xa0010}, {0x10840, 0xa0010}, {0x241, 0xa0010}, {0x20541, 0xa0010}, {0x403c1, 0xa0010}, {0x212c0, 0xa0010}, {0x602c1, 0xa0010}, {0xc2, 0xa0010}, {0x31040, 0xa0010}, {0x40040, 0xa0010}, {0x40d40, 0xa0010}, {0x417c0, 0xa0010}, {0x50a40, 0xa0010}, {0x51240, 0xa0010}, {0x60240, 0xa0010}, {0x60cc0, 0xa0010}, {0x614c0, 0xa0010}, {0x70740, 0xa0010}, {0x70f40, 0xa0010}, {0x20401c3, 0x200432}, {0x20401c4, 0x200432}, {0x20601a3, 0x200632}, {0x14e8223, 0xd0773}, {0x20601a4, 0x200632}, {0x14e8224, 0xd0773}, {0x22701a3, 0xe0875}, {0x22701a4, 0xe0875}, {0x5, 0x0}},
    {{0x8ea0, 0xa0010}, {0x108c0, 0xa0010}, {0x2c1, 0xa0010}, {0x205c1, 0xa0010}, {0x40441, 0xa0010}, {0x21340, 0xa0010}, {0x60341, 0xa0010}, {0x142, 0xa0010}, {0x310c0, 0xa0010}, {0x400c0, 0xa0010}, {0x40dc0, 0xa0010}, {0x50040, 0xa0010}, {0x50ac0, 0xa0010}, {0x512c0, 0xa0010}, {0x602c0, 0xa0010}, {0x60d40, 0xa0010}, {0x61540, 0xa0010}, {0x707c0, 0xa0010}, {0x70fc0, 0xa0010}, {0x2040243, 0x200432}, {0x2040244, 0x200432}, {0x2060223, 0x200632}, {0x1b68023, 0xe0774}, {0x2060224, 0x200632}, {0x1b68024, 0xe0774}, {0x2270223, 0xe0875}, {0x2270224, 0xe0875}, {0x5, 0x0}},
    {{0x8f20, 0xa0010}, {0x10940, 0xa0010}, {0x341, 0xa0010}, {0x20641, 0xa0010}, {0x404c1, 0xa0010}, {0x213c0, 0xa0010}, {0x603c1, 0xa0010}, {0x1c2, 0xa0010}, {0x31140, 0xa0010}, {0x40140, 0xa0010}, {0x40e40, 0xa0010}, {0x500c0, 0xa0010}, {0x50b40, 0xa0010}, {0x51340, 0xa0010}, {0x60340, 0xa0010}, {0x60dc0, 0xa0010}, {0x615c0, 0xa0010}, {0x70840, 0xa0010}, {0x71040, 0xa0010}, {0x715c0, 0xa0010}, {0x2050043, 0x200532}, {0x2050044, 0x200532}, {0x29680a3, 0xe0776}, {0x29680a4, 0xe0776}, {0x2970023, 0xe0876}, {0x2970024, 0xe0876}, {0x5, 0x0}},
    {{0x8fa0, 0xa0010}, {0x109c0, 0xa0010}, {0x3c1, 0xa0010}, {0x206c1, 0xa0010}, {0x40541, 0xa0010}, {0x21440, 0xa0010}, {0x60441, 0xa0010}, {0x242, 0xa0010}, {0x311c0, 0xa0010}, {0x401c0, 0xa0010}, {0x40ec0, 0xa0010}, {0x50140, 0xa0010}, {0x50bc0, 0xa0010}, {0x513c0, 0xa0010}, {0x603c0, 0xa0010}, {0x60e40, 0xa0010}, {0x61640, 0xa0010}, {0x708c0, 0xa0010}, {0x710c0, 0xa0010}, {0x71640, 0xa0010}, {0x20500c3, 0x200532}, {0x20500c4, 0x200532}, {0x2968123, 0xe0776}, {0x2968124, 0xe0776}, {0x29700a3, 0xe0876}, {0x29700a4, 0xe0876}, {0x5, 0x0}},
    {{0x9020, 0xa0010}, {0x41, 0xa0010}, {0x441, 0xa0010}, {0x20741, 0xa0010}, {0x405c1, 0xa0010}, {0x214c0, 0xa0010}, {0x604c1, 0xa0010}, {0x302c0, 0xa0010}, {0x10042, 0xa0010}, {0x40240, 0xa0010}, {0x40f40, 0xa0010}, {0x501c0, 0xa0010}, {0x50c40, 0xa0010}, {0x51440, 0xa0010}, {0x60440, 0xa0010}, {0x60ec0, 0xa0010}, {0x616c0, 0xa0010}, {0x70940, 0xa0010}, {0x71140, 0xa0010}, {0x716c0, 0xa0010}, {0x2050143, 0x200532}, {0x2050144, 0x200532}, {0x29681a3, 0xe0776}, {0x29681a4, 0xe0776}, {0x2970123, 0xe0876}, {0x2970124, 0xe0876}, {0x5, 0x0}},
    {{0x90a0, 0xa0010}, {0xc1, 0xa0010}, {0x4c1, 0xa0010}, {0x30041, 0xa0010}, {0x40641, 0xa0010}, {0x21540, 0xa0010}, {0x60541, 0xa0010}, {0x30340, 0xa0010}, {0x100c2, 0xa0010}, {0x402c0, 0xa0010}, {0x40fc0, 0xa0010}, {0x50240, 0xa0010}, {0x50cc0, 0xa0010}, {0x514c0, 0xa0010}, {0x604c0, 0xa0010}, {0x60f40, 0xa0010}, {0x61740, 0xa0010}, {0x709c0, 0xa0010}, {0x711c0, 0xa0010}, {0x71740, 0xa0010}, {0x20501c3, 0x200532}, {0x20501c4, 0x200532}, {0x2968223, 0xe0776}, {0x2968224, 0xe0776}, {0x29701a3, 0xe0876}, {0x29701a4, 0xe0876}, {0x5, 0x0}},
    {{0x9120, 0xa0010}, {0x141, 0xa0010}, {0x541, 0xa0010}, {0x300c1, 0xa0010}, {0x406c1, 0xa0010}, {0x215c0, 0xa0010}, {0x605c1, 0xa0010}, {0x303c0, 0xa0010}, {0x10142, 0xa0010}, {0x40340, 0xa0010}, {0x41040, 0xa0010}, {0x502c0, 0xa0010}, {0x50d40, 0xa0010}, {0x51540, 0xa0010}, {0x60540, 0xa0010}, {0x60fc0, 0xa0010}, {0x617c0, 0xa0010}, {0x70a40, 0xa0010}, {0x71240, 0xa0010}, {0x717c0, 0xa0010}, {0x2050243, 0x200532}, {0x2050244, 0x200532}, {0x2970223, 0xe0876}, {0x2970224, 0xe0876}, {0x5, 0x0}},
    {{0x91a0, 0xa0010}, {0x1c1, 0xa0010}, {0x5c1, 0xa0010}, {0x30141, 0xa0010}, {0x40741, 0xa0010}, {0x21640, 0xa0010}, {0x60641, 0xa0010}, {0x30440, 0xa0010}, {0x101c2, 0xa0010}, {0x403c0, 0xa0010}, {0x410c0, 0xa0010}, {0x50340, 0xa0010}, {0x50dc0, 0xa0010}, {0x515c0, 0xa0010}, {0x605c0, 0xa0010}, {0x61040, 0xa0010}, {0x70040, 0xa0010}, {0x70ac0, 0xa0010}, {0x712c0, 0xa0010}, {0x6e8023, 0xe0771}, {0x6e8024, 0xe0771}, {0x5, 0x0}}
}};
#define D8(i) "+f"(d[i]), "+f"(d[i + 1]), "+f"(d[i + 2]), "+f"(d[i + 3]), "+f"(d[i + 4]), "+f"(d[i + 5]), "+f"(d[i + 6]), "+f"(d[i + 7])
template <int N> __device__ __forceinline__ void wgmma_side(float* d, uint32_t alo, uint32_t blo, int sc);
template <> __device__ __forceinline__ void wgmma_side<128>(float* d, uint32_t alo, uint32_t blo, int sc) {
    asm volatile("{.reg .pred p; .reg .b64 ad, bd; setp.ne.b32 p, %66, 0; mov.b64 ad, {%64, 0x40000040}; mov.b64 bd, {%65, 0x40000040};\n"
                 "wgmma.mma_async.sync.aligned.m64n128k16.f32.bf16.bf16 "
                 "{%0,%1,%2,%3,%4,%5,%6,%7,%8,%9,%10,%11,%12,%13,%14,%15,%16,%17,%18,%19,%20,%21,%22,%23,%24,%25,%26,%27,%28,%29,%30,%31,"
                 "%32,%33,%34,%35,%36,%37,%38,%39,%40,%41,%42,%43,%44,%45,%46,%47,%48,%49,%50,%51,%52,%53,%54,%55,%56,%57,%58,%59,%60,%61,%62,%63},"
                 " ad, bd, p, 1, 1, 1, 0;}"
                 : D8(0), D8(8), D8(16), D8(24), D8(32), D8(40), D8(48), D8(56)
                 : "r"(alo), "r"(blo), "r"(sc));
}
template <> __device__ __forceinline__ void wgmma_side<192>(float* d, uint32_t alo, uint32_t blo, int sc) {
    asm volatile("{.reg .pred p; .reg .b64 ad, bd; setp.ne.b32 p, %98, 0; mov.b64 ad, {%96, 0x40000040}; mov.b64 bd, {%97, 0x40000040};\n"
                 "wgmma.mma_async.sync.aligned.m64n192k16.f32.bf16.bf16 "
                 "{%0,%1,%2,%3,%4,%5,%6,%7,%8,%9,%10,%11,%12,%13,%14,%15,%16,%17,%18,%19,%20,%21,%22,%23,%24,%25,%26,%27,%28,%29,%30,%31,"
                 "%32,%33,%34,%35,%36,%37,%38,%39,%40,%41,%42,%43,%44,%45,%46,%47,%48,%49,%50,%51,%52,%53,%54,%55,%56,%57,%58,%59,%60,%61,%62,%63,"
                 "%64,%65,%66,%67,%68,%69,%70,%71,%72,%73,%74,%75,%76,%77,%78,%79,%80,%81,%82,%83,%84,%85,%86,%87,%88,%89,%90,%91,%92,%93,%94,%95},"
                 " ad, bd, p, 1, 1, 1, 0;}"
                 : D8(0), D8(8), D8(16), D8(24), D8(32), D8(40), D8(48), D8(56), D8(64), D8(72), D8(80), D8(88)
                 : "r"(alo), "r"(blo), "r"(sc));
}
template <> __device__ __forceinline__ void wgmma_side<256>(float* d, uint32_t alo, uint32_t blo, int sc) {
    asm volatile("{.reg .pred p; .reg .b64 ad, bd; setp.ne.b32 p, %130, 0; mov.b64 ad, {%128, 0x40000040}; mov.b64 bd, {%129, 0x40000040};\n"
                 "wgmma.mma_async.sync.aligned.m64n256k16.f32.bf16.bf16 "
                 "{%0,%1,%2,%3,%4,%5,%6,%7,%8,%9,%10,%11,%12,%13,%14,%15,%16,%17,%18,%19,%20,%21,%22,%23,%24,%25,%26,%27,%28,%29,%30,%31,"
                 "%32,%33,%34,%35,%36,%37,%38,%39,%40,%41,%42,%43,%44,%45,%46,%47,%48,%49,%50,%51,%52,%53,%54,%55,%56,%57,%58,%59,%60,%61,%62,%63,"
                 "%64,%65,%66,%67,%68,%69,%70,%71,%72,%73,%74,%75,%76,%77,%78,%79,%80,%81,%82,%83,%84,%85,%86,%87,%88,%89,%90,%91,%92,%93,%94,%95,"
                 "%96,%97,%98,%99,%100,%101,%102,%103,%104,%105,%106,%107,%108,%109,%110,%111,%112,%113,%114,%115,%116,%117,%118,%119,%120,%121,%122,%123,%124,%125,%126,%127},"
                 " ad, bd, p, 1, 1, 1, 0;}"
                 : D8(0), D8(8), D8(16), D8(24), D8(32), D8(40), D8(48), D8(56), D8(64), D8(72), D8(80), D8(88), D8(96), D8(104), D8(112), D8(120)
                 : "r"(alo), "r"(blo), "r"(sc));
}
#undef D8

__device__ __forceinline__ void bulk_st(void* dst, uint32_t src, uint32_t bytes) {
    asm volatile("cp.async.bulk.global.shared::cta.bulk_group [%0], [%1], %2;" :: "l"(dst), "r"(src), "r"(bytes) : "memory");
}
__device__ __forceinline__ void red_release(uint32_t* p, uint32_t v) { asm volatile("red.release.gpu.global.add.u32 [%0], %1;" :: "l"(p), "r"(v) : "memory"); }
__device__ __forceinline__ void wait_ge(const uint32_t* p, uint32_t v) { for (int c = 0; c < SPIN_LIM && (int)(ld_acquire(p) - v) < 0; c++) { } }
__device__ __forceinline__ uint4* part_ptr(Job job, int wg) {
    return g_op + (size_t)((job.x >> 13) & 63) * (10 * NKS * 256) + (((job.x >> 7) & 63) * 2 + wg) * NKS * ((job.x >> 3) & 15) * 256;
}

template <int T>
__device__ __forceinline__ void side_job(Job job, uint32_t& it, uint32_t& n, uint32_t sb, uint32_t sa, int wg, int t)
{
    float acc[T / 2];
#pragma unroll
    for (int i = 0; i < T / 2; i++) acc[i] = 0.f;
    const int nkb = job.y >> 16;
    constexpr uint32_t NS = SST, SZ = S_STAGE, BO = 0;
    uint32_t prev = 0;
    for (int kb = 0; kb < nkb; kb++, it++) {
        const uint32_t st = it % NS;
        const uint32_t alo = ((sb + st * SZ + wg * 8192) >> 4) | (64u << 16), blo = ((sb + st * SZ + 16384) >> 4) | (1u << 16);
        mbar_wait_long(sb + SB_FULL + BO + 8 * st, (it / NS) & 1);
        wg_fence();
#pragma unroll
        for (int k4 = 0; k4 < 4; k4++) wgmma_side<T>(acc, alo + k4 * 128, blo + k4 * 2, kb | k4);
        wg_commit();
        if (kb) { wg_wait<1>(); arrive_e(prev); }
        prev = sb + SB_EMPTY + BO + 8 * st;
    }
    if (n) mbar_wait_long(sb + SB_FREE, (n - 1) & 1);
    n++;
    wg_wait<0>();
    arrive_e(prev);
    const bool raw = (job.x & 7) == JV || (job.y & 0xf0) != 0x10;
#pragma unroll
    for (int u = 0; u < T / 16; u++) {
        const uint4 w = make_uint4(pack2(acc[8 * u], acc[8 * u + 1]), pack2(acc[8 * u + 2], acc[8 * u + 3]),
                                   pack2(acc[8 * u + 4], acc[8 * u + 5]), pack2(acc[8 * u + 6], acc[8 * u + 7]));
        if (raw || T != 256) sts4(sb + S_STG + wg * 32768 + t * 16 + u * 2048, w);
        else stsm4t(sb + S_STG + wg * 32768 + sa + u * 2048, w.x, w.y, w.z, w.w);
    }
    asm volatile("fence.proxy.async.shared::cta;" ::: "memory");
    __syncwarp();
    arrive_e(sb + SB_STAGED + 8 * wg);
}

template <int NS>
__device__ __forceinline__ void side_sum(Job job, uint32_t& n, uint32_t sb, uint32_t sa, int wg, int t)
{
    constexpr int NU = (16 + NS - 1) / NS;
    const int ks = job.y & 15, nb = (job.x >> 3) & 15;
    const uint4* part = part_ptr(job, wg) + ks * 128 + t;
    uint4 q[NU][NS];
#pragma unroll
    for (int i = 0; i < NU; i++) {
#pragma unroll
        for (int k = 0; k < NS; k++) q[i][k] = make_uint4(0, 0, 0, 0);
        if (ks + i * NS < 2 * nb) {
#pragma unroll
            for (int k = 0; k < NS; k++) q[i][k] = ld_pkt(part + k * nb * 256 + i * NS * 128);
        }
    }
    if (n) mbar_wait_long(sb + SB_FREE, (n - 1) & 1);
    n++;
#pragma unroll
    for (int i = 0; i < NU; i++)
        if (ks + i * NS < 2 * nb) {
            float r[8] = {0, 0, 0, 0, 0, 0, 0, 0};
#pragma unroll
            for (int k = 0; k < NS; k++) {
                r[0] += bf_lo(q[i][k].x); r[1] += bf_hi(q[i][k].x); r[2] += bf_lo(q[i][k].y); r[3] += bf_hi(q[i][k].y);
                r[4] += bf_lo(q[i][k].z); r[5] += bf_hi(q[i][k].z); r[6] += bf_lo(q[i][k].w); r[7] += bf_hi(q[i][k].w);
            }
            stsm4t(sb + S_STG + wg * 32768 + sa + i * 2048, pack2(r[0], r[1]), pack2(r[2], r[3]), pack2(r[4], r[5]), pack2(r[6], r[7]));
        }
    asm volatile("fence.proxy.async.shared::cta;" ::: "memory");
    __syncwarp();
    arrive_e(sb + SB_STAGED + 8 * wg);
}

__device__ __forceinline__ void ld20(const bf16* p, uint32_t* w) {
#pragma unroll
    for (int i = 0; i < 5; i++) asm volatile("ld.global.v2.b32 {%0,%1}, [%2];" : "=r"(w[2 * i]), "=r"(w[2 * i + 1]) : "l"(p + 4 * i) : "memory");
}

__global__ void __launch_bounds__(384, 1) side_kernel(const __grid_constant__ SideParams P)
{
    extern __shared__ __align__(1024) uint8_t smem[];
    const uint32_t sb = smem_u32(smem);
    const int tid = threadIdx.x, lane = tid & 31;
    const int warp = __shfl_sync(0xffffffffu, tid >> 5, 0);
    if (tid == 0) {
        TLS(96 + blockIdx.x, 71);
        for (int i = 0; i < SST; i++) { mbar_init(sb + SB_FULL + 8 * i, 1); mbar_init(sb + SB_EMPTY + 8 * i, 8); }
        mbar_init(sb + SB_STAGED, 4); mbar_init(sb + SB_STAGED + 8, 4); mbar_init(sb + SB_FREE, 1);
        asm volatile("fence.mbarrier_init.release.cluster;" ::: "memory");
    }
    __syncthreads();
#ifdef NOSIDE
    { const uint32_t ep = ld_epoch(); asm volatile("griddepcontrol.wait;" ::: "memory"); if (blockIdx.x == 0 && tid == 0) g_epoch = ep; return; }
#endif
    const Job* jobs = c_jobs.j[blockIdx.x];
    if (warp < 8) {
        asm volatile("setmaxnreg.inc.sync.aligned.u32 192;");
        const uint32_t ep = ld_epoch();
        uint32_t it = 0, n = 0;
        const int wg = warp >> 2, t = tid & 127;
        const uint32_t sa = ((lane & 7) + ((lane >> 4) << 3)) * 128 + (((2 * (t >> 5) + ((lane >> 3) & 1)) ^ (lane & 7)) << 4);
        for (int j = 0; ; j++) {
            const Job job = jobs[j];
            if (tid == 0) TLS(96 + blockIdx.x, j);
            const int type = job.x & 7, nb = (job.x >> 3) & 15;
            if (type == JEND) break;
            if (type == JR) {
                const int ns = (job.y >> 4) & 15;
                if (t == 0) wait_ge(g_cnt + CNT_O + ((job.y >> 8) & 255) * 5 + ((job.x >> 7) & 63), ep * ns);
                bar_sync(1 + wg, 128);
                switch (ns) {
                    case 2: side_sum<2>(job, n, sb, sa, wg, t); break;
                    case 3: side_sum<3>(job, n, sb, sa, wg, t); break;
                    case 4: side_sum<4>(job, n, sb, sa, wg, t); break;
                    default: side_sum<7>(job, n, sb, sa, wg, t); break;
                }
                continue;
            }
            switch (nb) {
                case 8: side_job<256>(job, it, n, sb, sa, wg, t); break;
                case 6: side_job<192>(job, it, n, sb, sa, wg, t); break;
                default: side_job<128>(job, it, n, sb, sa, wg, t); break;
            }
        }

        if (tid == 0) TLS(96 + blockIdx.x, 70);
    } else {
        asm volatile("setmaxnreg.dec.sync.aligned.u32 120;");
        if (warp == 8) {
            const uint32_t ns = SST, sz = S_STAGE, bo = sb;
            uint32_t ep = 0, sa = 0, pa = 1, sl = 0;
            for (int j = 0; ; j++) {
                const Job job = jobs[j];
                const int type = job.x & 7;
                if (type == JEND) break;
                if (type == JR) continue;
                const int nb = (job.x >> 3) & 15, c0 = ((job.x >> 7) & 63) * 128, seg0 = (job.x >> 13) & 63, kb0 = (job.x >> 19) & 127,
                          nkb = job.y >> 16;
                const CUtensorMap *ta = &P.a[type], *tb = nb == 8 ? &P.b[type] : &P.c[type];
                const int nbox = nb == 8 ? 1 : nb;
                auto ready = [&]() {
                    bool ok = true;
                    if (type == JP) ok = (int)(ld_acquire(g_cnt + CNT_ATT + (seg0 >> 3)) - ep * 256) >= 0;
                    else for (int i = lane; i < nkb; i += 32) ok &= (int)(ld_acquire(g_prog + kb0 + i) - (ep * 128 + seg0 + nb)) >= 0;
                    return __all_sync(0xffffffffu, ok);
                };
                auto loadA = [&](int kb) {
                    const uint32_t full = bo + SB_FULL + 8 * sa;
                    mbar_wait_long(bo + SB_EMPTY + 8 * sa, pa);
                    expect_e(full, 16384 + nb * 4096);
                    tma2d_e(sb + sa * sz, ta, c0, (kb0 + kb) * 64, full);
                    tma2d_e(sb + sa * sz + 8192, ta, c0 + 64, (kb0 + kb) * 64, full);
                    if (++sa == ns) { sa = 0; pa ^= 1; }
                };
                auto loadB = [&](int kb) {
                    for (int i = 0; i < nbox; i++)
                        tma2d_e(sb + sl * sz + 16384 + i * 4096, tb, (kb0 + kb) * 64, (seg0 + i) * 32, bo + SB_FULL + 8 * sl);
                    if (++sl == ns) sl = 0;
                };
                int pre = 0;
                if (type >= JP) {
                    if (!ready()) {
                        pre = ns;
#pragma unroll 1
                        for (int kb = 0; kb < pre; kb++) loadA(kb);
                        for (int c = 0; c < SPIN_LIM && !ready(); c++) { }
                    }
                    if (lane == 0) TLS(96 + blockIdx.x, 53);
                    asm volatile("fence.proxy.async.global;" ::: "memory");
                    if (lane == 0) TLS(96 + blockIdx.x, 54);
                }
#pragma unroll 1
                for (int kb = 0; kb < nkb; kb++) { if (kb >= pre) loadA(kb); loadB(kb); }
                if (j == 0) ep = ld_epoch();
            }
            asm volatile("griddepcontrol.wait;" ::: "memory");
            if (blockIdx.x == 0 && lane == 0) g_epoch = ep;
        } else if (warp == 9) {
            if (lane == 0) {
                const uint32_t ep = ld_epoch();
                uint32_t n = 0;
                for (int j = 0; ; j++) {
                    const Job job = jobs[j];
                    const int type = job.x & 7;
                    if (type == JEND) break;
                    const int nb = (job.x >> 3) & 15, ct = (job.x >> 7) & 63, seg0 = (job.x >> 13) & 63, ns = (job.y >> 4) & 15;
                    for (int wg = 0; wg < 2; wg++) {
                        const uint32_t src = sb + S_STG + wg * 32768;
                        mbar_wait_long(sb + SB_STAGED + 8 * wg, n & 1);
                        if (type == JV) bulk_st(g_vx + ((ct * 2 + wg) * 64 + seg0) * 256, src, nb * 4096);
                        else if (type == JR) {
                            for (int u = job.y & 15, i = 0; u < 2 * nb; u += ns, i++) tma_st(&P.sto, src + i * 2048, DM + ct * 128 + wg * 64, seg0 * 32 + u * 16);
                        } else if (ns > 1) bulk_st(part_ptr(job, wg) + (job.y & 15) * nb * 256, src, nb * 4096);
                        else tma_st(&P.st[type != JQ], src, (type == JO ? DM : 0) + ct * 128 + wg * 64, seg0 * 32);
                    }
                    asm volatile("cp.async.bulk.commit_group;" ::: "memory");
                    asm volatile("cp.async.bulk.wait_group.read 0;" ::: "memory");
                    mbar_arrive(sb + SB_FREE);
                    asm volatile("cp.async.bulk.wait_group 0;" ::: "memory");
                    if (type == JV) { st_release(g_flagv + ct * 128 + seg0, ep); g_flagv[ct * 128 + 64 + seg0] = ep; }
                    if (type == JQ) red_release(g_cnt + CNT_Q + (seg0 >> 3), 1);
                    if (type == JO && ns > 1) red_release(g_cnt + CNT_O + ((job.y >> 8) & 255) * 5 + ct, 1);
                    n++;
                }
            }
        } else {
            const uint32_t ep = ld_epoch();
            const float scl = 0.22360679774997896f * 1.4426950408889634f;
            for (int p = blockIdx.x * 2 + warp - 10; p < SEQ / 2; p += 2 * NSIDE) {
                const int t0 = 4 * (p >> 1) + (p & 1);
                wait_ge(g_cnt + CNT_Q + (max(t0 - 14, 0) >> 8), ep * 15);
                wait_ge(g_cnt + CNT_Q + (t0 >> 8), ep * 15);
                const bf16* base = g_qkvA + lane * 20;
                uint32_t w[18][10];
                auto row = [&](int j) { if (j < 18) ld20(base + (size_t)max(t0 + 2 - 2 * (j % 9), 0) * 1920 + (j < 9 ? 640 : 1280), w[j]); };
                float l0[8], l1[8];
                {
                    uint32_t u0[10], u1[10];
                    float q0[20], q1[20];
                    ld20(base + (size_t)t0 * 1920, u0); ld20(base + (size_t)(t0 + 2) * 1920, u1);
                    row(0); row(1);
#pragma unroll
                    for (int i = 0; i < 10; i++) { q0[2 * i] = bf_lo(u0[i]); q0[2 * i + 1] = bf_hi(u0[i]); q1[2 * i] = bf_lo(u1[i]); q1[2 * i + 1] = bf_hi(u1[i]); }
#pragma unroll
                    for (int j = 0; j < 9; j++) {
                        row(j + 2);
                        blk(warp);
                        float a0 = 0.f, a1 = 0.f;
#pragma unroll
                        for (int i = 0; i < 10; i++) {
                            const float lo = bf_lo(w[j][i]), hi = bf_hi(w[j][i]);
                            if (j > 0) a0 = fmaf(q0[2 * i + 1], hi, fmaf(q0[2 * i], lo, a0));
                            if (j < 8) a1 = fmaf(q1[2 * i + 1], hi, fmaf(q1[2 * i], lo, a1));
                        }
                        const bool in = t0 + 2 - 2 * j >= 0;
                        if (j > 0) l0[j - 1] = in ? a0 * scl : -3.0e38f;
                        if (j < 8) l1[j] = in ? a1 * scl : -3.0e38f;
                    }
                }
                float m0 = l0[0], m1 = l1[0], s0 = 0.f, s1 = 0.f;
#pragma unroll
                for (int j = 1; j < 8; j++) { m0 = fmaxf(m0, l0[j]); m1 = fmaxf(m1, l1[j]); }
#pragma unroll
                for (int j = 0; j < 8; j++) { l0[j] = ex2(l0[j] - m0); s0 += l0[j]; l1[j] = ex2(l1[j] - m1); s1 += l1[j]; }
                float o0[20], o1[20];
#pragma unroll
                for (int i = 0; i < 20; i++) o0[i] = o1[i] = 0.f;
#pragma unroll
                for (int j = 0; j < 9; j++) {
                    row(j + 11);
                    blk(warp);
#pragma unroll
                    for (int i = 0; i < 10; i++) {
                        const float lo = bf_lo(w[9 + j][i]), hi = bf_hi(w[9 + j][i]);
                        if (j > 0) { o0[2 * i] = fmaf(l0[j - 1], lo, o0[2 * i]); o0[2 * i + 1] = fmaf(l0[j - 1], hi, o0[2 * i + 1]); }
                        if (j < 8) { o1[2 * i] = fmaf(l1[j], lo, o1[2 * i]); o1[2 * i + 1] = fmaf(l1[j], hi, o1[2 * i + 1]); }
                    }
                }
                s0 = 1.f / s0; s1 = 1.f / s1;
                uint2* dst = reinterpret_cast<uint2*>(g_oA + (size_t)t0 * DM + lane * 20);
#pragma unroll
                for (int i = 0; i < 5; i++) {
                    dst[i] = make_uint2(pack2(o0[4 * i] * s0, o0[4 * i + 1] * s0), pack2(o0[4 * i + 2] * s0, o0[4 * i + 3] * s0));
                    dst[i + 2 * DM / 4] = make_uint2(pack2(o1[4 * i] * s1, o1[4 * i + 1] * s1), pack2(o1[4 * i + 2] * s1, o1[4 * i + 3] * s1));
                }
                __syncwarp();
                if (lane == 0) red_release(g_cnt + CNT_ATT + (t0 >> 8), 2);
                if (tid == 320) TLS(96 + blockIdx.x, 44 + p / 144);
            }
        }
    }
}

typedef CUresult (*EncodeFn)(CUtensorMap*, CUtensorMapDataType, cuuint32_t, void*, const cuuint64_t*, const cuuint64_t*,
                             const cuuint32_t*, const cuuint32_t*, CUtensorMapInterleave, CUtensorMapSwizzle,
                             CUtensorMapL2promotion, CUtensorMapFloatOOBfill);
static void make_map(EncodeFn enc, CUtensorMap* tm, const void* ptr, uint64_t cols, uint64_t rows, uint32_t bc, uint32_t br,
                     CUtensorMapSwizzle sw = CU_TENSOR_MAP_SWIZZLE_128B) {
    cuuint64_t dims[2] = {cols, rows}, strides[1] = {cols * 2};
    cuuint32_t box[2] = {bc, br}, es[2] = {1, 1};
    enc(tm, CU_TENSOR_MAP_DATA_TYPE_BFLOAT16, 2, const_cast<void*>(ptr), dims, strides, box, es, CU_TENSOR_MAP_INTERLEAVE_NONE, sw,
        CU_TENSOR_MAP_L2_PROMOTION_L2_128B, CU_TENSOR_MAP_FLOAT_OOB_FILL_NONE);
}

extern "C" void kernel_launch(void* const* d_in, const int* in_sizes, int n_in, void* d_out, int out_size) {
    (void)in_sizes; (void)n_in; (void)out_size;
    const bf16* A_x = (const bf16*)d_in[0];
    const bf16* A_wqkv = (const bf16*)d_in[1];
    const bf16* A_wo = (const bf16*)d_in[2];
    const bf16* B_x = (const bf16*)d_in[3];
    const bf16* B_mem0 = (const bf16*)d_in[4];
    const bf16* B_Wq = (const bf16*)d_in[5];
    const bf16* B_Wk = (const bf16*)d_in[6];
    const bf16* B_Wv = (const bf16*)d_in[7];
    const bf16* B_Wo = (const bf16*)d_in[8];
    bf16* out = (bf16*)d_out;

    static EncodeFn enc = nullptr;
    static void *p_ox, *p_qkv, *p_oA, *p_xch;
    if (!enc) {
        void* fn = nullptr; cudaDriverEntryPointQueryResult qr;
        cudaGetDriverEntryPoint("cuTensorMapEncodeTiled", &fn, cudaEnableDefault, &qr);
        enc = (EncodeFn)fn;
        cudaFuncSetAttribute(chain_kernel, cudaFuncAttributeMaxDynamicSharedMemorySize, CHAIN_SMEM);
        cudaFuncSetAttribute(side_kernel, cudaFuncAttributeMaxDynamicSharedMemorySize, SIDE_SMEM);
        cudaGetSymbolAddress(&p_ox, g_ox); cudaGetSymbolAddress(&p_qkv, g_qkvA); cudaGetSymbolAddress(&p_oA, g_oA);
        cudaGetSymbolAddress(&p_xch, g_xch);
    }
    CUtensorMap tmX, tmX7, tmWq, tmWk, tmWv, tmWo, tmWb;
    {
        cuuint64_t dims[3] = {64, SEQ, 10}, strides[2] = {DM * 2, 128};
        cuuint32_t box[3] = {64, 32, NX}, es[3] = {1, 1, 1};
        enc(&tmX7, CU_TENSOR_MAP_DATA_TYPE_BFLOAT16, 3, const_cast<bf16*>(B_x), dims, strides, box, es, CU_TENSOR_MAP_INTERLEAVE_NONE, CU_TENSOR_MAP_SWIZZLE_128B,
            CU_TENSOR_MAP_L2_PROMOTION_L2_128B, CU_TENSOR_MAP_FLOAT_OOB_FILL_NONE);
    }
    make_map(enc, &tmX, B_x, DM, SEQ, 64, 32);
    make_map(enc, &tmWq, B_Wq, HE, DM, 64, 128);
    make_map(enc, &tmWk, B_Wk, HE, DM, 64, 128);
    make_map(enc, &tmWv, B_Wv, HE, DM, 64, 128);
    make_map(enc, &tmWo, B_Wo, DM, HE, 64, 64);
    make_map(enc, &tmWb, B_Wo, DM, HE, 16, 64, CU_TENSOR_MAP_SWIZZLE_32B);
    SideParams sp;
    make_map(enc, &sp.a[JV], B_Wv, HE, DM, 64, 64);
    make_map(enc, &sp.a[JQ], A_wqkv, 3 * DM, DM, 64, 64);
    make_map(enc, &sp.a[JP], A_wo, DM, DM, 64, 64);
    sp.a[JO] = tmWo;
    const void* act[4] = {B_x, A_x, p_oA, p_ox};
    for (int i = 0; i < 4; i++) {
        make_map(enc, &sp.b[i], act[i], i == JO ? HE : DM, SEQ, 64, 256);
        make_map(enc, &sp.c[i], act[i], i == JO ? HE : DM, SEQ, 64, 32);
    }
    make_map(enc, &sp.st[0], p_qkv, 3 * DM, SEQ, 64, 256);
    make_map(enc, &sp.st[1], out, OUTW, SEQ, 64, 256);
    make_map(enc, &sp.sto, out, OUTW, SEQ, 64, 16);

    cudaStream_t st = cudaStreamPerThread;
    chain_kernel<<<96, 512, CHAIN_SMEM, st>>>(tmX, tmX7, tmWq, tmWk, tmWv, tmWo, tmWb, sp.c[JO], B_mem0, (const char*)B_x,
                                              (const char*)(((uintptr_t)p_xch + 0x1fffff) & ~(uintptr_t)0x1fffff), out);
    cudaLaunchConfig_t cfg = {};
    cfg.gridDim = dim3(NSIDE); cfg.blockDim = dim3(384); cfg.dynamicSmemBytes = SIDE_SMEM; cfg.stream = st;
    cudaLaunchAttribute at[1];
    at[0].id = cudaLaunchAttributeProgrammaticStreamSerialization; at[0].val.programmaticStreamSerializationAllowed = 1;
    cfg.attrs = at; cfg.numAttrs = 1;
    cudaLaunchKernelEx(&cfg, side_kernel, sp);
}

#ifdef TL
extern "C" void tc_read(void* dst) { cudaMemcpyFromSymbol(dst, g_tc, sizeof(g_tc)); }
extern "C" void tl_read(void* dst, void* jobs) { cudaMemcpyFromSymbol(dst, g_tl, sizeof(g_tl)); cudaMemcpyFromSymbol(jobs, c_jobs, sizeof(c_jobs)); }
#endif
#ifdef DEV
extern "C" void dev_read(void* dst, int which) {
    if (which == 0) cudaMemcpyFromSymbol(dst, g_dbg, sizeof(g_dbg));
    if (which == 1) cudaMemcpyFromSymbol(dst, g_ox, sizeof(g_ox));
    if (which == 3) cudaMemcpyFromSymbol(dst, g_cal, sizeof(g_cal));
    if (which == 5) cudaMemcpyToSymbol(g_s0, dst, 4);
    if (which == 4) {
        void* p; cudaGetSymbolAddress(&p, g_pp); cudaMemset(p, 0, sizeof(g_pp));
        cudaFuncSetAttribute(calib_kernel, cudaFuncAttributeMaxDynamicSharedMemorySize, 200000);
        calib_kernel<<<132, 32, 200000>>>(); cudaDeviceSynchronize();
        cudaMemcpyFromSymbol(dst, g_off, sizeof(g_off));
    }
}
#endif
```

```cpp
#include <cuda_runtime.h>
#include <cuda_bf16.h>
#include <cuda.h>
#include <stdint.h>
#include <string.h>
#include <type_traits>

typedef __nv_bfloat16 bf16;

constexpr int SEQ = 2048, DM = 640, NH = 32, DH = 192, HE = NH * DH;
constexpr int NSEG = 64;
constexpr int OUTW = 1280;

__device__ uint4 g_xch[(4 << 20) / 16];
__device__ uint4 g_near4[96 * 2];
__device__ bf16  g_ox[SEQ * HE];
__device__ bf16  g_qkvA[SEQ * 3 * DM];
__device__ bf16  g_oA[SEQ * DM];
__device__ uint4 g_vx[96 * NSEG * 256];
__device__ uint4 g_op[NSEG * 70 * 256];
__device__ uint4 g_tail[4 * 32 * 80 * 32];
__device__ uint32_t g_epoch;
__device__ uint32_t g_flagv[96 * 64];
__device__ uint32_t g_prog[96];
__device__ uint32_t g_cnt[256];
constexpr int CNT_Q = 0, CNT_ATT = 8, CNT_O = 16, SPIN_LIM = 1 << 15;
#ifdef TL
__device__ uint32_t g_tl[132 * 80];
__device__ uint32_t g_tc[132 * 80];
__device__ uint32_t g_ev[4 * 64];
#define EVT(k) asm volatile("{.reg .pred p; elect.sync _|p, 0xffffffff; @p st.global.u32 [%0], %1;}" :: "l"(g_ev + (k) * 64 + s), "r"(lds1(sb + OFF_EP)) : "memory")
#define TLS(row, i) do { uint32_t t_, c_; asm volatile("mov.u32 %0, %%globaltimer_lo; mov.u32 %1, %%clock;" : "=r"(t_), "=r"(c_)); g_tl[(row) * 80 + (i)] = t_; g_tc[(row) * 80 + (i)] = c_; } while (0)
#define TLC(w, i) do { if (warp == (w)) asm volatile("{.reg .b32 t; mov.u32 t, %%globaltimer_lo; st.shared.b32 [%0], t; mov.u32 t, %%clock; st.shared.b32 [%0 + 4], t;}" :: "r"(sb + OFF_DBG + (i) * 8) : "memory"); } while (0)
#else
#define TLS(row, i) do { } while (0)
#define TLC(w, i) do { } while (0)
#define EVT(k) do { } while (0)
#endif
#ifdef DEV
__device__ uint32_t g_dbg[96 * 512];
__device__ uint32_t g_cal[96 * 8];
#endif

__device__ __forceinline__ uint32_t smem_u32(const void* p) { return (uint32_t)__cvta_generic_to_shared(p); }
__device__ __forceinline__ uint32_t pack2(float lo, float hi) {
    uint32_t r; asm("cvt.rn.bf16x2.f32 %0, %1, %2;" : "=r"(r) : "f"(hi), "f"(lo)); return r;
}
__device__ __forceinline__ float ex2(float x) { float r; asm("ex2.approx.ftz.f32 %0, %1;" : "=f"(r) : "f"(x)); return r; }
__device__ __forceinline__ float rcpf(float x) { float r; asm("rcp.approx.ftz.f32 %0, %1;" : "=f"(r) : "f"(x)); return r; }
__device__ __forceinline__ void mbar_init(uint32_t bar, uint32_t cnt) {
    asm volatile("mbarrier.init.shared::cta.b64 [%0], %1;" :: "r"(bar), "r"(cnt) : "memory");
}
__device__ __forceinline__ void mbar_arrive(uint32_t bar) {
    asm volatile("mbarrier.arrive.shared::cta.b64 _, [%0];" :: "r"(bar) : "memory");
}
__device__ __forceinline__ void mbar_expect(uint32_t bar, uint32_t bytes) {
    asm volatile("mbarrier.arrive.expect_tx.shared::cta.b64 _, [%0], %1;" :: "r"(bar), "r"(bytes) : "memory");
}
constexpr int WAIT_LIM = 2048;
__device__ __forceinline__ void mbar_wait(uint32_t bar, uint32_t parity) {
    asm volatile("{.reg .pred p, q; .reg .u32 c; mov.u32 c, 512;\n"
                 "WL_%=: mbarrier.try_wait.parity.shared::cta.b64 p, [%0], %1;\n"
                 "@p bra WD_%=; sub.u32 c, c, 1; setp.ne.u32 q, c, 0; @q bra WL_%=;\n"
                 "WD_%=: }" :: "r"(bar), "r"(parity) : "memory");
}
__device__ __forceinline__ void mbar_wait_long(uint32_t bar, uint32_t parity) {
    asm volatile("{.reg .pred p, q; .reg .u32 c; mov.u32 c, 16384;\n"
                 "WL_%=: mbarrier.try_wait.parity.shared::cta.b64 p, [%0], %1;\n"
                 "@p bra WD_%=; sub.u32 c, c, 1; setp.ne.u32 q, c, 0; @q bra WL_%=;\n"
                 "WD_%=: }" :: "r"(bar), "r"(parity) : "memory");
}
__device__ __forceinline__ void bar_sync(int id, int n) { asm volatile("bar.sync %0, %1;" :: "r"(id), "r"(n) : "memory"); }
__device__ __forceinline__ void bar_arrive(int id, int n) { asm volatile("bar.arrive %0, %1;" :: "r"(id), "r"(n) : "memory"); }
__device__ __forceinline__ void tma2d(uint32_t dst, const CUtensorMap* tm, int c0, int c1, uint32_t bar) {
    asm volatile("cp.async.bulk.tensor.2d.shared::cluster.global.mbarrier::complete_tx::bytes [%0], [%1, {%3, %4}], [%2];"
                 :: "r"(dst), "l"(tm), "r"(bar), "r"(c0), "r"(c1) : "memory");
}
__device__ __forceinline__ void tma_st(const CUtensorMap* tm, uint32_t src, int c0, int c1) {
    asm volatile("cp.async.bulk.tensor.2d.global.shared::cta.bulk_group [%0, {%2, %3}], [%1];" :: "l"(tm), "r"(src), "r"(c0), "r"(c1) : "memory");
}
__device__ __forceinline__ void ldsm4(uint32_t a, uint32_t& r0, uint32_t& r1, uint32_t& r2, uint32_t& r3) {
    asm volatile("ldmatrix.sync.aligned.m8n8.x4.shared.b16 {%0,%1,%2,%3}, [%4];"
                 : "=r"(r0), "=r"(r1), "=r"(r2), "=r"(r3) : "r"(a) : "memory");
}
__device__ __forceinline__ void ldsm4t(uint32_t a, uint32_t& r0, uint32_t& r1, uint32_t& r2, uint32_t& r3) {
    asm volatile("ldmatrix.sync.aligned.m8n8.x4.trans.shared.b16 {%0,%1,%2,%3}, [%4];"
                 : "=r"(r0), "=r"(r1), "=r"(r2), "=r"(r3) : "r"(a) : "memory");
}
__device__ __forceinline__ void ldsm2t(uint32_t a, uint32_t& r0, uint32_t& r1) {
    asm volatile("ldmatrix.sync.aligned.m8n8.x2.trans.shared.b16 {%0,%1}, [%2];" : "=r"(r0), "=r"(r1) : "r"(a) : "memory");
}
__device__ __forceinline__ void stsm4t(uint32_t a, uint32_t r0, uint32_t r1, uint32_t r2, uint32_t r3) {
    asm volatile("stmatrix.sync.aligned.m8n8.x4.trans.shared.b16 [%0], {%1,%2,%3,%4};"
                 :: "r"(a), "r"(r0), "r"(r1), "r"(r2), "r"(r3) : "memory");
}
__device__ __forceinline__ void stsm2t(uint32_t a, uint32_t r0, uint32_t r1) {
    asm volatile("stmatrix.sync.aligned.m8n8.x2.trans.shared.b16 [%0], {%1,%2};" :: "r"(a), "r"(r0), "r"(r1) : "memory");
}
__device__ __forceinline__ void stsm4(uint32_t a, uint32_t r0, uint32_t r1, uint32_t r2, uint32_t r3) {
    asm volatile("stmatrix.sync.aligned.m8n8.x4.shared.b16 [%0], {%1,%2,%3,%4};" :: "r"(a), "r"(r0), "r"(r1), "r"(r2), "r"(r3) : "memory");
}
__device__ __forceinline__ void stsm2(uint32_t a, uint32_t r0, uint32_t r1) {
    asm volatile("stmatrix.sync.aligned.m8n8.x2.shared.b16 [%0], {%1,%2};" :: "r"(a), "r"(r0), "r"(r1) : "memory");
}
__device__ __forceinline__ uint32_t movm(uint32_t a) {
    uint32_t d; asm volatile("movmatrix.sync.aligned.m8n8.trans.b16 %0, %1;" : "=r"(d) : "r"(a)); return d;
}
__device__ __forceinline__ void mma16(float* c, uint32_t a0, uint32_t a1, uint32_t a2, uint32_t a3, uint32_t b0, uint32_t b1) {
    asm volatile("mma.sync.aligned.m16n8k16.row.col.f32.bf16.bf16.f32 {%0,%1,%2,%3}, {%4,%5,%6,%7}, {%8,%9}, {%0,%1,%2,%3};"
                 : "+f"(c[0]), "+f"(c[1]), "+f"(c[2]), "+f"(c[3]) : "r"(a0), "r"(a1), "r"(a2), "r"(a3), "r"(b0), "r"(b1));
}
__device__ __forceinline__ void mma8(float* c, uint32_t a0, uint32_t a1, uint32_t b0) {
    asm volatile("mma.sync.aligned.m16n8k8.row.col.f32.bf16.bf16.f32 {%0,%1,%2,%3}, {%4,%5}, {%6}, {%0,%1,%2,%3};"
                 : "+f"(c[0]), "+f"(c[1]), "+f"(c[2]), "+f"(c[3]) : "r"(a0), "r"(a1), "r"(b0));
}
__device__ __forceinline__ void wg_fence() { asm volatile("wgmma.fence.sync.aligned;" ::: "memory"); }
__device__ __forceinline__ void wg_commit() { asm volatile("wgmma.commit_group.sync.aligned;" ::: "memory"); }
template <int N> __device__ __forceinline__ void wg_wait() { asm volatile("wgmma.wait_group.sync.aligned %0;" :: "n"(N) : "memory"); }
__device__ __forceinline__ uint64_t mkdesc(uint32_t addr, uint32_t lbo, uint32_t sbo, uint32_t swz) {
    return (uint64_t)((addr & 0x3FFFF) >> 4) | ((uint64_t)(lbo >> 4) << 16) | ((uint64_t)(sbo >> 4) << 32) | ((uint64_t)swz << 62);
}
template <int BOFF, int SC>
__device__ __forceinline__ void wgmma_rs16(float* d, uint32_t a0, uint32_t a1, uint32_t a2, uint32_t a3, uint32_t blo) {
    asm volatile("{.reg .pred p; .reg .b32 l; .reg .b64 bd; setp.ne.b32 p, %14, 0; add.u32 l, %12, %13; mov.b64 bd, {l, 40};\n"
                 "wgmma.mma_async.sync.aligned.m64n16k16.f32.bf16.bf16 {%0,%1,%2,%3,%4,%5,%6,%7}, {%8,%9,%10,%11}, bd, p, 1, 1, 0;}"
                 : "+f"(d[0]), "+f"(d[1]), "+f"(d[2]), "+f"(d[3]), "+f"(d[4]), "+f"(d[5]), "+f"(d[6]), "+f"(d[7])
                 : "r"(a0), "r"(a1), "r"(a2), "r"(a3), "r"(blo), "n"(BOFF), "n"(SC));
}
template <int BOFF, int SC>
__device__ __forceinline__ void wgmma_rs32(float* d, uint32_t a0, uint32_t a1, uint32_t a2, uint32_t a3, uint32_t blo) {
    asm volatile("{.reg .pred p; .reg .b32 l; .reg .b64 bd; setp.ne.b32 p, %22, 0; add.u32 l, %20, %21; mov.b64 bd, {l, 0x40000040};\n"
                 "wgmma.mma_async.sync.aligned.m64n32k16.f32.bf16.bf16 "
                 "{%0,%1,%2,%3,%4,%5,%6,%7,%8,%9,%10,%11,%12,%13,%14,%15}, {%16,%17,%18,%19}, bd, p, 1, 1, 0;}"
                 : "+f"(d[0]), "+f"(d[1]), "+f"(d[2]), "+f"(d[3]), "+f"(d[4]), "+f"(d[5]), "+f"(d[6]), "+f"(d[7]),
                   "+f"(d[8]), "+f"(d[9]), "+f"(d[10]), "+f"(d[11]), "+f"(d[12]), "+f"(d[13]), "+f"(d[14]), "+f"(d[15])
                 : "r"(a0), "r"(a1), "r"(a2), "r"(a3), "r"(blo), "n"(BOFF), "n"(SC));
}
template <int AOFF, int BOFF, int SC>
__device__ __forceinline__ void wgmma_ss32(float* d, uint32_t alo, uint32_t blo) {
    asm volatile("{.reg .pred p; .reg .b32 l, m; .reg .b64 ad, bd; setp.ne.b32 p, %20, 0; add.u32 l, %16, %18; add.u32 m, %17, %19;\n"
                 "mov.b64 ad, {l, 0x40000040}; mov.b64 bd, {m, 0x40000040};\n"
                 "wgmma.mma_async.sync.aligned.m64n32k16.f32.bf16.bf16 "
                 "{%0,%1,%2,%3,%4,%5,%6,%7,%8,%9,%10,%11,%12,%13,%14,%15}, ad, bd, p, 1, 1, 1, 0;}"
                 : "+f"(d[0]), "+f"(d[1]), "+f"(d[2]), "+f"(d[3]), "+f"(d[4]), "+f"(d[5]), "+f"(d[6]), "+f"(d[7]),
                   "+f"(d[8]), "+f"(d[9]), "+f"(d[10]), "+f"(d[11]), "+f"(d[12]), "+f"(d[13]), "+f"(d[14]), "+f"(d[15])
                 : "r"(alo), "r"(blo), "n"(AOFF), "n"(BOFF), "n"(SC));
}
template <int AOFF, int BOFF, int SC>
__device__ __forceinline__ void wgmma_ss8(float* d, uint32_t alo, uint32_t blo) {
    asm volatile("{.reg .pred p; .reg .b32 l, m; .reg .b64 ad, bd; setp.ne.b32 p, %8, 0; add.u32 l, %4, %6; add.u32 m, %5, %7;\n"
                 "mov.b64 ad, {l, 0x40000040}; mov.b64 bd, {m, 0};\n"
                 "wgmma.mma_async.sync.aligned.m64n8k16.f32.bf16.bf16 {%0,%1,%2,%3}, ad, bd, p, 1, 1, 1, 1;}"
                 : "+f"(d[0]), "+f"(d[1]), "+f"(d[2]), "+f"(d[3]) : "r"(alo), "r"(blo), "n"(AOFF), "n"(BOFF), "n"(SC));
}
template <int OFF, int SC>
__device__ __forceinline__ void wgmma_ss40(float* d, uint32_t alo, uint32_t blo) {
    asm volatile("{.reg .pred p; .reg .b32 l, m; .reg .b64 ad, bd; setp.ne.b32 p, %23, 0; add.u32 l, %20, %22; add.u32 m, %21, %22;\n"
                 "mov.b64 ad, {l, 0x40000020}; mov.b64 bd, {m, 0x40000040};\n"
                 "wgmma.mma_async.sync.aligned.m64n40k16.f32.bf16.bf16 "
                 "{%0,%1,%2,%3,%4,%5,%6,%7,%8,%9,%10,%11,%12,%13,%14,%15,%16,%17,%18,%19}, ad, bd, p, 1, 1, 0, 0;}"
                 : "+f"(d[0]), "+f"(d[1]), "+f"(d[2]), "+f"(d[3]), "+f"(d[4]), "+f"(d[5]), "+f"(d[6]), "+f"(d[7]),
                   "+f"(d[8]), "+f"(d[9]), "+f"(d[10]), "+f"(d[11]), "+f"(d[12]), "+f"(d[13]), "+f"(d[14]), "+f"(d[15]),
                   "+f"(d[16]), "+f"(d[17]), "+f"(d[18]), "+f"(d[19])
                 : "r"(alo), "r"(blo), "n"(OFF), "n"(SC));
}
template <int I> using IC = std::integral_constant<int, I>;
template <int I, int N, class F> __device__ __forceinline__ void static_for(F&& f) {
    if constexpr (I < N) { f(std::integral_constant<int, I>{}); static_for<I + 1, N>(f); }
}
__device__ __forceinline__ uint32_t mapa(uint32_t a, uint32_t rank) {
    uint32_t r, c; asm("mov.u32 %0, %%cluster_ctarank;" : "=r"(c));
    asm("mapa.shared::cluster.u32 %0, %1, %2;" : "=r"(r) : "r"(a), "r"(rank + (c > 2 ? 3 : 0))); return r;
}
__device__ __forceinline__ void st_async2(uint32_t a, uint32_t x, uint32_t y, uint32_t bar) {
    asm volatile("st.async.weak.shared::cluster.mbarrier::complete_tx::bytes.v2.b32 [%0], {%1,%2}, [%3];"
                 :: "r"(a), "r"(x), "r"(y), "r"(bar) : "memory");
}
__device__ __forceinline__ void st_async1(uint32_t a, uint32_t x, uint32_t bar) {
    asm volatile("st.async.weak.shared::cluster.mbarrier::complete_tx::bytes.b32 [%0], %1, [%2];" :: "r"(a), "r"(x), "r"(bar) : "memory");
}
__device__ __forceinline__ void st_async4(uint32_t a, uint32_t x, uint32_t y, uint32_t z, uint32_t w, uint32_t bar) {
    asm volatile("st.async.weak.shared::cluster.mbarrier::complete_tx::bytes.v4.b32 [%0], {%1,%2,%3,%4}, [%5];"
                 :: "r"(a), "r"(x), "r"(y), "r"(z), "r"(w), "r"(bar) : "memory");
}
__device__ __forceinline__ void sts2(uint32_t a, uint32_t x, uint32_t y) {
    asm volatile("st.shared.v2.b32 [%0], {%1,%2};" :: "r"(a), "r"(x), "r"(y) : "memory");
}
__device__ __forceinline__ void sts4(uint32_t a, uint4 v) {
    asm volatile("st.shared.v4.b32 [%0], {%1,%2,%3,%4};" :: "r"(a), "r"(v.x), "r"(v.y), "r"(v.z), "r"(v.w) : "memory");
}
__device__ __forceinline__ void sts1(uint32_t a, uint32_t x) { asm volatile("st.shared.b32 [%0], %1;" :: "r"(a), "r"(x) : "memory"); }
__device__ __forceinline__ float2 lds2f(uint32_t a) {
    float2 v; asm volatile("ld.shared.v2.f32 {%0,%1}, [%2];" : "=f"(v.x), "=f"(v.y) : "r"(a) : "memory"); return v;
}
__device__ __forceinline__ uint4 lds4(uint32_t a) {
    uint4 v; asm volatile("ld.shared.v4.b32 {%0,%1,%2,%3}, [%4];" : "=r"(v.x), "=r"(v.y), "=r"(v.z), "=r"(v.w) : "r"(a) : "memory"); return v;
}
__device__ __forceinline__ uint32_t lds1(uint32_t a) {
    uint32_t v; asm volatile("ld.shared.b32 %0, [%1];" : "=r"(v) : "r"(a) : "memory"); return v;
}
__device__ __forceinline__ void stg1(void* p, uint32_t x) { asm volatile("st.global.b32 [%0], %1;" :: "l"(p), "r"(x) : "memory"); }
__device__ __forceinline__ uint32_t ld_acquire(const uint32_t* p) {
    uint32_t v; asm volatile("ld.acquire.gpu.global.u32 %0, [%1];" : "=r"(v) : "l"(p) : "memory"); return v;
}
__device__ __forceinline__ uint32_t ld_relaxed(const void* p) {
    uint32_t v; asm volatile("ld.relaxed.gpu.global.u32 %0, [%1];" : "=r"(v) : "l"(p) : "memory"); return v;
}
__device__ __forceinline__ uint32_t ld_epoch() {
    uint32_t v; asm volatile("ld.relaxed.gpu.global.u32 %0, [%1];" : "=r"(v) : "l"(&g_epoch) : "memory"); return v + 1;
}
__device__ __forceinline__ void st_release(uint32_t* p, uint32_t v) { asm volatile("st.release.gpu.global.u32 [%0], %1;" :: "l"(p), "r"(v) : "memory"); }
__device__ __forceinline__ void st_pkt8(const void* p, uint32_t x, uint32_t y) {
    asm volatile("{.reg .b64 v; mov.b64 v, {%1,%2}; st.relaxed.gpu.global.b64 [%0], v;}" :: "l"(p), "r"(x), "r"(y) : "memory");
}
__device__ __forceinline__ void st_pkt4(const void* p, uint32_t x) {
    asm volatile("st.relaxed.gpu.global.b32 [%0], %1;" :: "l"(p), "r"(x) : "memory");
}
__device__ __forceinline__ uint4 ld_pkt(const void* p) {
    uint4 r;
    asm volatile("{.reg .b64 lo, hi; .reg .b128 v; ld.relaxed.gpu.global.b128 v, [%4]; mov.b128 {lo, hi}, v;\n"
                 "mov.b64 {%0,%1}, lo; mov.b64 {%2,%3}, hi;}"
                 : "=r"(r.x), "=r"(r.y), "=r"(r.z), "=r"(r.w) : "l"(p) : "memory");
    return r;
}

template <int OFF> __device__ __forceinline__ void ld_pkt8(uint32_t& x, uint32_t& y, const void* p) {
    asm volatile("{.reg .b64 v; ld.relaxed.gpu.global.b64 v, [%2 + %3]; mov.b64 {%0,%1}, v;}" : "=r"(x), "=r"(y) : "l"(p), "n"(OFF) : "memory");
}
template <int OFF> __device__ __forceinline__ void ld_pkt8_stale(uint32_t& x, uint32_t& y, const void* p, uint32_t tag) {
    asm volatile("{.reg .pred p; .reg .b32 t; .reg .b64 v; lop3.b32 t, %0, %3, 1, 0x28; setp.ne.u32 p, t, 0; mov.b64 v, {%0,%1};\n"
                 "@p ld.relaxed.gpu.global.b64 v, [%2 + %4]; mov.b64 {%0,%1}, v;}" : "+r"(x), "+r"(y) : "l"(p), "r"(tag), "n"(OFF) : "memory");
}
template <int OFF> __device__ __forceinline__ void ld_pkt_stale(uint4& r, const void* p, uint32_t tag) {
    asm volatile("{.reg .pred p; .reg .b32 t; .reg .b64 lo, hi; .reg .b128 v; lop3.b32 t, %0, %5, 1, 0x28; setp.ne.u32 p, t, 0;\n"
                 "mov.b64 lo, {%0,%1}; mov.b64 hi, {%2,%3}; mov.b128 v, {lo, hi}; @p ld.relaxed.gpu.global.b128 v, [%4 + %6];\n"
                 "mov.b128 {lo, hi}, v; mov.b64 {%0,%1}, lo; mov.b64 {%2,%3}, hi;}"
                 : "+r"(r.x), "+r"(r.y), "+r"(r.z), "+r"(r.w) : "l"(p), "r"(tag), "n"(OFF) : "memory");
}

constexpr int NX = 7;
constexpr uint32_t SB0 = 1024;
constexpr uint32_t HALF = 40960, OFF_WV = 0, OFF_WO = 81920, OFF_QX = OFF_WO + 36864, OFF_Q0 = OFF_WO + 90112, OFF_K0 = OFF_Q0 + 1024,
                   OFF_XR = OFF_K0 + 1024, OFF_SX = OFF_XR + NX * 4096, OFF_OX = OFF_SX, OFF_PX = OFF_SX + 5120, OFF_VM = OFF_SX,
                   OFF_SP = OFF_PX + 2560, OFF_Q1 = OFF_SP + 2560, OFF_K1 = OFF_Q1 + 1024, OFF_KX = OFF_K1 + 1024,
                   OFF_MEMT = OFF_KX + 4096, OFF_SM = OFF_MEMT + 10240, OFF_PM = OFF_SM + 1280, OFF_BAR = OFF_PM + 768,
                   OFF_DBG = OFF_BAR + 320, CHAIN_SMEM = OFF_DBG + 704,
                   OFF_SXL = OFF_XR, OFF_OXL = OFF_SXL, OFF_OXG = OFF_XR + 9216, OFF_TRED = OFF_WV + 65536, OFF_OXE = OFF_WV + 32768;
static_assert(OFF_Q1 == OFF_Q0 + HALF && CHAIN_SMEM <= 232448, "layout");
__host__ __device__ constexpr uint32_t wo_b(uint32_t j) { return OFF_WO + 24576 + j * 6144 + (j > 1 ? 28672 : 0); }
__host__ __device__ constexpr uint32_t tile_b(uint32_t u) { return u + (u < 8 ? 12 : 24); }
__host__ __device__ constexpr uint32_t xblk(int kb) { return kb < 3 ? OFF_MEMT - OFF_XR + kb * 4096 : (kb - 3) * 4096; }
constexpr uint32_t MB_S = OFF_BAR, MB_SX = OFF_BAR + 8, MB_O = OFF_BAR + 16, MB_WO = OFF_BAR + 24, MB_XA = OFF_BAR + 32,
                   MB_XB = OFF_BAR + 40, MB_EN = OFF_BAR + 80, MB_EM = OFF_BAR + 88, MB_EA = OFF_BAR + 96, MB_EL = OFF_BAR + 104, OFF_ZERO = OFF_BAR + 112, OFF_EP = OFF_BAR + 116, OFF_KP = OFF_BAR + 120,
                   MB_F = OFF_BAR + 128, MB_E = OFF_BAR + 168, OFF_INV = OFF_BAR + 224, OFF_PRB = OFF_BAR + 256, OFF_TG = OFF_BAR + 264, MB_G = OFF_BAR + 272, OFF_RL = OFF_BAR + 48, MB_H = MB_G + 32,
                   OFF_R0 = OFF_SP + 512, OFF_R1 = OFF_Q0;
constexpr int BAR_K = 0, BAR_PUB = 1, BAR_QK = 2, BAR_P = 3, BAR_WO = 4, BAR_S = 5, BAR_V = 6, BAR_O = 7, BAR_R = 8, BAR_PM = 9, BAR_SX = 10,
              BAR_Q = 11, BAR_X = 15, BAR_QJ = BAR_O, BAR_SR = 12, BAR_OR = 13, BAR_OF = 14;
__host__ __device__ constexpr int bar_g(int i, int w) { return i + w < 2 ? 12 + 2 * i + w : BAR_PM; }
constexpr float SCL_B = 0.07216878364870322f * 1.4426950408889634f;
#ifndef DEFN
#define DEFN 1
#endif
#ifndef ZG
#define ZG 1
#endif
#ifndef NAC
#define NAC 3
#endif
#ifndef WOE
#define WOE 1
#endif
#ifndef TX0
#define TX0 1
#endif
#ifndef PATT
#define PATT "UUUUUUOURUUOURUOURUOURUOUROROROROORR"
#endif
#ifndef HOME
#define HOME 1
#endif
#ifndef SW
#define SW 3
#endif
#ifndef NPROBE
#define NPROBE 3
#endif
#ifdef TUNE
__constant__ int c_tune[16];
extern "C" void tune_set(const int* v) { cudaMemcpyToSymbol(c_tune, v, 64); }
#define DLY1 c_tune[0]
#define STG1 c_tune[1]
#define STG2 c_tune[2]
#define STG3 c_tune[3]
#define STG4 c_tune[4]
#define H0 c_tune[5]
#define H1 c_tune[6]
#define H2 c_tune[7]
#define H3 c_tune[8]
#define DLYN c_tune[9]
#define HS c_tune[10]
#define KPT c_tune[11]
#define H4 c_tune[12]
#endif
#ifndef STG1
#define STG1 230
#endif
#ifndef KPT
#define KPT 0x99
#endif
#ifndef DLYN
#define DLYN 610
#endif
#ifndef DLY1
#define DLY1 1320
#endif
#ifndef STG2
#define STG2 280
#endif
#ifndef STG3
#define STG3 280
#endif
#ifndef STG4
#define STG4 300
#endif
#ifndef OPT
#define OPT 1
#endif
#ifndef PVB
#define PVB 1
#endif
#ifndef HS
#define HS 0
#endif
#ifndef XG
#define XG 2
#endif
#ifndef EAS
#define EAS 0
#endif
#ifndef BJ
#define BJ 3
#endif
#ifndef CJ
#define CJ 7
#endif
#ifndef OJ
#define OJ 9
#endif
#ifndef H4
#define H4 830
#endif
#ifndef H0
#define H0 2510
#endif
#ifndef H1
#define H1 2470
#endif
#ifndef H2
#define H2 2900
#endif
#ifndef H3
#define H3 2820
#endif
#ifndef NVC
#define NVC 4
#endif
#ifndef PWIN
#define PWIN 3
#endif
#ifndef KP0
#define KP0 5
#endif
#ifndef FNC
#define FNC 1
#endif
#ifndef VG
#define VG 0
#endif
#ifndef EMW
#define EMW 1
#endif
#ifndef SJ
#define SJ 9
#endif
#ifndef WP
#define WP 0
#endif
#ifndef VW
#define VW 1
#endif
#ifndef VN
#define VN 0
#endif
#ifndef MG
#define MG 1
#endif
#ifndef WE
#define WE 1
#endif
#ifndef RM
#define RM 1
#endif
#ifndef VE
#define VE 2
#endif
#ifndef OD
#define OD 2
#endif
#ifndef WS
#define WS 1
#endif
#ifndef PAUSE
#define PAUSE 0
#endif
#ifndef XO
#define XO 0
#endif
#ifndef VL
#define VL 0
#endif
#ifndef GS
#define GS 1
#endif
#ifndef TG
#define TG 1
#endif
#ifndef XC
#define XC 0
#endif
#ifndef PFX
#define PFX 1
#endif
#ifndef AE
#define AE 4
#endif
#ifndef SR
#define SR 1
#endif
#ifndef W1
#define W1 6
#endif
#ifndef W2
#define W2 W1
#endif
#ifndef W0
#define W0 2
#endif
#ifndef CL
#define CL 6
#endif
#ifndef BT
#define BT 1
#endif
#ifndef PF
#define PF 0
#endif
#ifndef LAG
#define LAG 5
#endif
#ifndef OP
#define OP 1
#endif
#ifndef CD
#define CD 1
#endif
#ifndef AP
#define AP 1
#endif
#ifndef AQ
#define AQ 0
#endif
#ifndef XR
#define XR 1
#endif
#ifndef XE
#define XE 3
#endif
#ifndef PD
#define PD 3
#endif
#ifndef GA
#define GA 0
#endif
#ifndef GH
#define GH 7
#endif
#ifndef WD
#define WD 1
#endif
#ifndef VF
#define VF 1
#endif
#ifndef NT
#define NT 4
#endif
#ifndef SD
#define SD 1
#endif
#ifndef BM0
#define BM0 0x3ff
#endif
#ifndef BM1
#define BM1 0x3ff
#endif
#ifndef VP
#define VP 0
#endif
#ifndef P0
#define P0 0
#endif
#ifndef P1
#define P1 0
#endif
#ifndef G1
#define G1 8
#endif
#ifndef WI
#define WI 0
#endif
#ifndef EPC
#define EPC 1
#endif
#ifndef PX0
#define PX0 1
#endif
#ifndef TM
#define TM 0
#endif
#ifndef TD3
#define TD3 1000
#endif
#ifndef TW
#define TW 1
#endif
#ifndef TD0
#define TD0 0
#endif
#ifndef TD1
#define TD1 0
#endif
#ifndef TD2
#define TD2 0
#endif
#ifndef BP
#define BP 0
#endif
#ifndef VS
#define VS 0
#endif
#ifndef XW
#define XW 0
#endif
#ifndef VD
#define VD 2
#endif

__device__ __forceinline__ uint32_t clk32() { uint32_t c; asm volatile("mov.u32 %0, %%clock;" : "=r"(c)); return c; }
__device__ __forceinline__ void spin(uint32_t n) { const uint32_t t = clk32(); while (clk32() - t < n) { } }
__device__ __forceinline__ uint32_t gtime() { uint64_t c; asm volatile("mov.u64 %0, %%globaltimer;" : "=l"(c)); return (uint32_t)c; }
__device__ __forceinline__ uint32_t clkv() { uint64_t c; asm volatile("mov.u64 %0, %%clock64;" : "=l"(c)); return (uint32_t)c; }
__device__ __forceinline__ void gate(uint32_t t) { while ((int)(clk32() - t) < 0) { } }
__device__ __forceinline__ void gatev(uint32_t t) { while ((int)(clkv() - t) < 0) { } }
__device__ __forceinline__ uint32_t keep(uint32_t x) { asm volatile("" : "+r"(x)); return x; }
template <class T> __device__ __forceinline__ T* keepp(T* p) { asm volatile("" : "+l"(p)); return p; }
__device__ __forceinline__ void sched() { asm volatile("bar.warp.sync 0xffffffff;" ::: "memory"); }
__device__ __forceinline__ void blk(int s) { asm volatile("{.reg .pred p; setp.gt.s32 p, %0, 1000; @p exit;}" :: "r"(s) : "memory"); }
__device__ __forceinline__ uint32_t selu(bool c, uint32_t a, uint32_t b) {
    uint32_t r; asm("{.reg .pred p; setp.ne.u32 p, %1, 0; selp.b32 %0, %2, %3, p;}" : "=r"(r) : "r"((uint32_t)c), "r"(a), "r"(b)); return r;
}
__device__ __forceinline__ float bf_lo(uint32_t w) { return __uint_as_float(w << 16); }
__device__ __forceinline__ float bf_hi(uint32_t w) { return __uint_as_float(w & 0xffff0000u); }
__device__ __forceinline__ uint32_t badd2(uint32_t a, uint32_t b) { uint32_t r; asm("add.rn.bf16x2 %0, %1, %2;" : "=r"(r) : "r"(a), "r"(b)); return r; }
__device__ __forceinline__ uint32_t tagx(uint32_t a, uint32_t b, uint32_t t) { uint32_t r; asm("lop3.b32 %0, %1, %2, %3, 0x7e;" : "=r"(r) : "r"(a), "r"(t), "r"(b)); return r; }
__device__ __forceinline__ uint32_t tagv(uint32_t a, uint32_t b, uint32_t t) { uint32_t r; asm volatile("lop3.b32 %0, %1, %2, %3, 0x7e;" : "=r"(r) : "r"(a), "r"(t), "r"(b)); return r; }
__device__ __forceinline__ uint32_t bit0(uint32_t a, uint32_t t) { uint32_t r; asm("lop3.b32 %0, %1, 0xfffffffe, %2, 0xe2;" : "=r"(r) : "r"(a), "r"(t)); return r; }
__device__ __forceinline__ uint32_t or3(uint32_t a, uint32_t b, uint32_t c) { uint32_t r; asm("lop3.b32 %0, %1, %2, %3, 0xfe;" : "=r"(r) : "r"(a), "r"(b), "r"(c)); return r; }
__device__ __forceinline__ bool any_bit0(uint32_t a, uint32_t b) {
    uint32_t r;
    asm volatile("{.reg .pred p; .reg .b32 t; lop3.b32 t, %1, 1, %2, 0xc8; setp.ne.u32 p, t, 0; vote.sync.any.pred p, p, 0xffffffff; selp.u32 %0, 1, 0, p;}"
                 : "=r"(r) : "r"(a), "r"(b));
    return r;
}
template <int N> __device__ __forceinline__ bool stale_or_arrive(uint32_t a, uint32_t b, uint32_t A) {
    uint32_t r;
    asm volatile("{.reg .pred p; .reg .b32 t; lop3.b32 t, %1, 1, %2, 0xc8; setp.ne.u32 p, t, 0; vote.sync.any.pred p, p, 0xffffffff;\n"
                 "@!p bar.arrive %3, %4; selp.u32 %0, 1, 0, p;}" : "=r"(r) : "r"(a), "r"(b), "r"(A), "n"(N) : "memory");
    return r;
}
template <int A> __device__ __forceinline__ bool bar_any(bool x) {
    uint32_t r;
    asm volatile("{.reg .pred p; setp.ne.u32 p, %1, 0; bar.red.or.pred p, %2, 128, p; selp.u32 %0, 1, 0, p;}" : "=r"(r) : "r"((uint32_t)x), "n"(A) : "memory");
    return r;
}
__device__ __forceinline__ uint4 ld_s4(uint32_t a) {
    uint4 v; asm volatile("ld.volatile.shared.v4.b32 {%0,%1,%2,%3}, [%4];" : "=r"(v.x), "=r"(v.y), "=r"(v.z), "=r"(v.w) : "r"(a) : "memory"); return v;
}
__device__ __forceinline__ void arrive_e(uint32_t bar) {
    asm volatile("{.reg .pred p; elect.sync _|p, 0xffffffff; @p mbarrier.arrive.shared::cta.b64 _, [%0];}" :: "r"(bar) : "memory");
}
__device__ __forceinline__ void expect_e(uint32_t bar, uint32_t bytes) {
    asm volatile("{.reg .pred p; elect.sync _|p, 0xffffffff; @p mbarrier.arrive.expect_tx.shared::cta.b64 _, [%0], %1;}" :: "r"(bar), "r"(bytes) : "memory");
}
__device__ __forceinline__ void tma2d_e(uint32_t dst, const CUtensorMap* tm, int c0, int c1, uint32_t bar) {
    asm volatile("{.reg .pred p; elect.sync _|p, 0xffffffff;\n"
                 "@p cp.async.bulk.tensor.2d.shared::cluster.global.mbarrier::complete_tx::bytes [%0], [%1, {%3, %4}], [%2];}"
                 :: "r"(dst), "l"(tm), "r"(bar), "r"(c0), "r"(c1) : "memory");
}
#ifdef DEV
__constant__ int g_s0;
#define DBGBASE const uint32_t dbg = sb + OFF_DBG + ((uint32_t)(s - g_s0) < 2 ? (s - g_s0) * 320 + warp * 20 : 640)
#ifdef GT
#define TSTAMP(i) do { if (GT >> (i) & 1) asm volatile("{.reg .b32 t; mov.u32 t, %%globaltimer_lo; st.shared.b16 [%0 + %1], t;}" :: "r"(dbg), "n"((i) * 2) : "memory"); } while (0)
#else
#define TSTAMP(i) asm volatile("{.reg .b32 t; mov.u32 t, %%clock; st.shared.b16 [%0 + %1], t;}" :: "r"(dbg), "n"((i) * 2) : "memory")
#endif
#define TVAL(i, v) asm volatile("st.shared.b16 [%0 + %1], %2;" :: "r"(dbg), "n"((i) * 2), "r"(v) : "memory")
#ifdef SST_
#define TS2(i) TSTAMP(i)
#define TS3(i) do { } while (0)
#else
#define TS2(i) do { } while (0)
#define TS3(i) TSTAMP(i)
#endif
#define TVAL0(i, v) g_cal[blockIdx.x * 8 + i] = v
__device__ __forceinline__ void calib(uint32_t* dst) {
    uint32_t g1, sm; asm volatile("mov.u32 %0, %%globaltimer_lo;" : "=r"(g1)); asm volatile("mov.u32 %0, %%smid;" : "=r"(sm));
    dst[0] = g1; dst[1] = clk32(); g_cal[blockIdx.x * 8 + 4] = sm;
}
__device__ uint32_t g_pp[132 * 32];
__device__ uint32_t g_off[132 * 2];
__global__ void calib_kernel() {
    uint32_t sm; asm volatile("mov.u32 %0, %%smid;" : "=r"(sm));
    if (threadIdx.x) return;
    if (sm == 0) {
        for (int i = 1; i < 132; i++) {
            uint32_t best = 0xffffffffu, off = 0;
            for (uint32_t r = 1; r <= 8; r++) {
                volatile uint32_t* l = g_pp + i * 32;
                const uint32_t t0 = clk32();
                l[0] = r;
                unsigned long long v = 0;
                for (int c = 0; c < 100000; c++) { v = *(volatile unsigned long long*)(l + 2); if ((uint32_t)v == r) break; }
                const uint32_t t1 = clk32();
                if (t1 - t0 < best) { best = t1 - t0; off = (uint32_t)(v >> 32) - (t0 + (t1 - t0) / 2); }
                spin(100 + 37 * r);
            }
            g_off[2 * i] = off; g_off[2 * i + 1] = best;
        }
        g_off[0] = 0; g_off[1] = 0;
    } else {
        volatile uint32_t* l = g_pp + sm * 32;
        for (uint32_t r = 1; r <= 8; r++) {
            for (int c = 0; c < 4000000; c++) if (l[0] == r) break;
            *(volatile unsigned long long*)(l + 2) = ((unsigned long long)clk32() << 32) | r;
        }
    }
}
#else
#define TS2(i) do { } while (0)
#define TS3(i) do { } while (0)
#define DBGBASE do { } while (0)
#define TSTAMP(i) do { } while (0)
#define TVAL(i, v) do { } while (0)
#define TVAL0(i, v) do { } while (0)
#endif

__device__ __forceinline__ uint32_t xch_page(uint32_t t, uint32_t h) { return t * 0x2000 + ((h ^ t ^ (t >> 3) ^ (t >> 4)) & 1) * 0x1000; }
constexpr uint32_t XCH_CLK = 0x148000;
__host__ __device__ constexpr uint32_t xch_mem(uint32_t t) { return 0x100000 + (t < 12 ? t * 256 : t < 20 ? 0x8000 + (t - 12) * 256 : t < 32 ? 0x4000 + (t - 20) * 256 : 0xc000 + (t - 32) * 256); }

__device__ __forceinline__ uint4 role_tab(uint32_t role, uint32_t side) {
    const uint32_t i = role >> 1, t = i < 12 ? i : i < 24 ? i + 8 : tile_b(i - 24);
    return make_uint4(xch_page(t, role & 1), xch_mem(t) + (role & 1) * 144, role < 48 ? DLY1 : role < 80 ? DLY1 + STG1 : 0, side * 4096);
}
constexpr unsigned long long PROG_MASK = 0xa222020202020200ull;
__device__ __forceinline__ bool prog_step(int s) { return (PROG_MASK | 3ull << 62) >> s & 1; }
__device__ __forceinline__ int pause_at(uint32_t role) { return role < 80 ? KPT >> (role < 48 ? 0 : 4) & 15 : 99; }

__device__ __forceinline__ void share_o(uint32_t sb, uint32_t rank, uint32_t src, uint32_t t) {
#pragma unroll
    for (uint32_t p = 1; p < 3; p++) {
        const uint32_t pb = mapa(sb, (rank + p) % 3);
        asm volatile("{.reg .pred p; elect.sync _|p, 0xffffffff;\n"
                     "@p cp.async.bulk.shared::cluster.shared::cta.mbarrier::complete_tx::bytes [%0], [%1], 4096, [%2];}"
                     :: "r"(pb + OFF_OXG + t * 8192 + (2 - p) * 4096), "r"(sb + src), "r"(pb + MB_F + 8 * t) : "memory");
    }
}

__device__ __forceinline__ void tail_sum(uint32_t sb, int t, int bar, bf16* out) {
    uint32_t u, c;
    asm volatile("mov.u32 %0, %%tid.x; mov.u32 %1, %%ctaid.x;" : "=r"(u), "=r"(c));
    if (c >= 80) return;
    const uint32_t g = (u >> 5) & 3, ln = u & 31, et = lds1(sb + OFF_EP);
    const uint4* rp = g_tail + (t * 32 + g * 8) * 2560 + c * 32 + ln;
    uint4 q[8];
#pragma unroll
    for (int i = 0; i < 8; i++) q[i] = ld_pkt(rp + 2560 * i);
    for (int cnt = 4 * WAIT_LIM; cnt; cnt--) {
        uint32_t bad = 0;
#pragma unroll
        for (int i = 0; i < 8; i++) bad |= q[i].x ^ et;
        if (!any_bit0(bad, bad)) break;
        static_for<0, 8>([&](auto I) { ld_pkt_stale<I.value * 40960>(q[I.value], rp, et); });
    }
    float r[8] = {0, 0, 0, 0, 0, 0, 0, 0};
#pragma unroll
    for (int i = 0; i < 8; i++) {
        r[0] += bf_lo(q[i].x); r[1] += bf_hi(q[i].x); r[2] += bf_lo(q[i].y); r[3] += bf_hi(q[i].y);
        r[4] += bf_lo(q[i].z); r[5] += bf_hi(q[i].z); r[6] += bf_lo(q[i].w); r[7] += bf_hi(q[i].w);
    }
    const uint32_t ra = sb + OFF_TRED + t * 4096 + ln * 8, rb = ra + g * 1024;
#pragma unroll
    for (int j = 0; j < 4; j++) sts2(ra + j * 1024 + g * 256, __float_as_uint(r[2 * j]), __float_as_uint(r[2 * j + 1]));
    bar_sync(bar, 128);
    const float2 x0 = lds2f(rb), x1 = lds2f(rb + 256), x2 = lds2f(rb + 512), x3 = lds2f(rb + 768);
    stg1(out + (size_t)((NSEG - 4 + t) * 32 + (c & 1) * 16 + (g >> 1) * 8 + (ln >> 2)) * OUTW + DM + (c >> 1) * 16 + (g & 1) * 8 + (ln & 3) * 2,
         movm(pack2((x0.x + x1.x) + (x2.x + x3.x), (x0.y + x1.y) + (x2.y + x3.y))));
}

#define LANE_REGS const uint32_t l16 = __shfl_sync(0xffffffffu, sb + (tid & 31) * 16, tid & 31); const int lane = (l16 - sb) >> 4

__global__ void __cluster_dims__(CL, 1, 1) __launch_bounds__(512, 1)
chain_kernel(const __grid_constant__ CUtensorMap tmX, const __grid_constant__ CUtensorMap tmX7, const __grid_constant__ CUtensorMap tmWq, const __grid_constant__ CUtensorMap tmWk,
             const __grid_constant__ CUtensorMap tmWv, const __grid_constant__ CUtensorMap tmWo, const __grid_constant__ CUtensorMap tmWb,
             const __grid_constant__ CUtensorMap tmOx, const bf16* __restrict__ mem0, const char* xin,
             const char* win,
             bf16* out)
{
    extern __shared__ __align__(1024) uint8_t smem[];
    const uint32_t sb = smem_u32(smem);
    if ((sb & 0x3FFFF) != SB0) __trap();
    const int tid = threadIdx.x;
    const int warp = __shfl_sync(0xffffffffu, tid >> 5, 0);
    const uint32_t rank = blockIdx.x % 3;
    const int head = blockIdx.x / 3;
    uint32_t* const g_near = reinterpret_cast<uint32_t*>(g_near4);
    const char* pp = win + 0x140000 + (blockIdx.x & 63) * 64 + (blockIdx.x >> 6) * 0x4000;
    if (tid >= 480 && tid < 496) st_pkt4(pp + (tid & 8) * 512 + (tid & 7) * 4, 0);
    const uint32_t ep0 = ld_relaxed(&g_epoch);
    if (tid >= 320 && tid < 400) asm volatile("prefetch.global.L2 [%0];" :: "l"(mem0 + (tid - 320) * 64));
    if (PX0 && tid >= 416 && tid < 416 + 4 * (PD - 1) && blockIdx.x < 80) asm volatile("prefetch.global.L2 [%0];" :: "l"(xin + 40960 + (blockIdx.x * (PD - 1) * 4 + tid - 416) * 128));

    if (tid == 384) {
        mbar_init(sb + MB_S, 3); mbar_init(sb + MB_SX, 1); mbar_init(sb + MB_O, 1); mbar_init(sb + MB_WO, 1);
        mbar_init(sb + MB_XA, 1); mbar_init(sb + MB_XB, 1); mbar_init(sb + MB_EM, 8); mbar_init(sb + MB_EN, 8); mbar_init(sb + MB_EL, 8); mbar_init(sb + MB_EA, 12);
        for (int i = 0; i < 5; i++) { mbar_init(sb + MB_F + 8 * i, 1); mbar_init(sb + MB_E + 8 * i, 8); mbar_init(sb + MB_G + 8 * i, 1); }
        sts1(sb + OFF_ZERO, 0); sts1(sb + OFF_TG, clk32());
        sts1(sb + OFF_KP, pause_at(blockIdx.x)); sts4(sb + OFF_RL, role_tab(blockIdx.x, 0));
        asm volatile("fence.mbarrier_init.release.cluster;" ::: "memory");
        asm volatile("fence.proxy.async.shared::cta;" ::: "memory");
        for (int i = 0; i < PWIN; i++) {
            mbar_expect(sb + MB_F + 8 * i, 32768);
            tma2d(sb + OFF_WV + i * 16384, &tmWq, head * DH + rank * 64, i * 128, sb + MB_F + 8 * i);
            tma2d(sb + OFF_WO + i * 16384, &tmWk, head * DH + rank * 64, i * 128, sb + MB_F + 8 * i);
        }
        mbar_expect(sb + MB_XA, 9 * 4096); mbar_expect(sb + MB_XB, 4096);
        for (int i = 0; i < 10; i++) tma2d(sb + OFF_XR + xblk(i), &tmX, i * 64, 0, sb + (i == 2 ? MB_XB : MB_XA));
        mbar_expect(sb + MB_WO, 49152 + (rank ? 5 : 6) * 6144);
    }
    TLC(10, 70);
    asm volatile("griddepcontrol.launch_dependents;" ::: "memory");
    __syncthreads();
    asm volatile("barrier.cluster.arrive.release.aligned;" ::: "memory");

    if (warp < 8) {
        asm volatile("setmaxnreg.inc.sync.aligned.u32 208;");
        LANE_REGS;
        const int w4 = warp & 3;
        const uint32_t st0 = __shfl_sync(0xffffffffu, sb + (warp >> 2) * 40960 + ((lane & 7) + ((lane >> 4) << 3)) * 128 +
                                                      (((2 * w4 + ((lane >> 3) & 1)) ^ (lane & 7)) << 4), lane);
        const uint32_t xr_lo = (((SB0 + OFF_XR) & 0x3FFFF) >> 4) | (1u << 16);
        const uint32_t ta = (warp >> 2) * 20 + rank * 4 + w4, tb = tile_b(3 * warp + rank);
        const bool two = 3 * warp + rank < 16;
        const int wg = __reduce_max_sync(0xffffffffu, (unsigned)tid >> 7);
        const uint32_t uo = __reduce_max_sync(0xffffffffu, OFF_Q0 - 1024 - ((unsigned)tid >> 7) * 5120), ub = __reduce_max_sync(0xffffffffu, wo_b((unsigned)tid >> 5) - ((unsigned)tid >> 7) * 5120);
        uint32_t lm = __shfl_sync(0xffffffffu, sb + (warp >> 2) * 5120 + ((lane & 7) + ((lane >> 4) << 3)) * 32 + (((lane >> 3) ^ (lane >> 2)) & 1) * 16, lane);
        uint32_t wq[80], wk[80];
        {
            if (wg) { arrive_e(sb + MB_E); arrive_e(sb + MB_E + 8); } else { arrive_e(sb + MB_E + 24); arrive_e(sb + MB_E + 32); }
#pragma unroll
            for (int k = 0; k < 20; k++) {
                if (k % 4 == 0) mbar_wait(sb + MB_F + ((wg * 20 + k) >> 3) * 8, 0);
                ldsm4t(st0 + (OFF_WV + k * 2048), wq[4 * k], wq[4 * k + 1], wq[4 * k + 2], wq[4 * k + 3]);
                ldsm4t(st0 + (OFF_WO + k * 2048), wk[4 * k], wk[4 * k + 1], wk[4 * k + 2], wk[4 * k + 3]);
                if (k % 4 == 3 && (k == 19 || (k & 4) >> 2 != wg)) arrive_e(sb + MB_E + ((wg * 20 + k) >> 3) * 8);
            }
        }
        asm volatile("barrier.cluster.wait.acquire.aligned;" ::: "memory");
        mbar_wait(sb + MB_E + 16, 0);
        TLC(0, 71);
        mbar_wait(sb + MB_XA, 0); mbar_wait(sb + MB_XB, 0);
        TLC(0, 72);

        uint32_t a[20][4];
#pragma unroll
        for (int k = 0; k < 16; k++) a[k >> 2][k & 3] = 0;

        for (int s = 0; ; s++) {
            DBGBASE;
            blk(warp);
            auto la = [&](int k) { ldsm4t(st0 + (OFF_WV + k * 2048), a[k][0], a[k][1], a[k][2], a[k][3]); blk(warp); };
            {
                auto bulk = [&](auto WG) {
                    constexpr int W = WG.value;
                    constexpr uint32_t own = (W ? OFF_KX : OFF_QX) - W * HALF, oth = (W ? OFF_QX : OFF_KX) - W * HALF;
                    float acc[16];
#pragma unroll
                    for (int i = 0; i < 16; i++) acc[i] = 0.f;
                    auto put = [&](uint32_t o) {
                        stsm4t(st0 + o, pack2(acc[0], acc[1]), pack2(acc[2], acc[3]), pack2(acc[4], acc[5]), pack2(acc[6], acc[7]));
                        stsm4t(st0 + (o + 2048), pack2(acc[8], acc[9]), pack2(acc[10], acc[11]), pack2(acc[12], acc[13]), pack2(acc[14], acc[15]));
                    };
                    uint32_t u[8], gt, gs;
                    auto get = [&]() {
                        bar_sync(W ? BAR_QJ : BAR_QK, 256);
                        ldsm4t(st0 + own, u[0], u[1], u[2], u[3]);
                        ldsm4t(st0 + (own + 2048), u[4], u[5], u[6], u[7]);
                    };
                    auto lv = [&](int k) { ldsm4t(st0 + (OFF_WV + k * 2048), a[k][0], a[k][1], a[k][2], a[k][3]); };
                    if constexpr (W && AQ == 4) { lv(0); lv(1); lv(2); lv(3); }
                    if constexpr (W && LAG) bar_sync(BAR_PUB, 256);
                    static_for<0, 10>([&](auto H) {
                        constexpr int h = H.value, kb = h < 5 ? (h + 3) % 5 : h - 5;
                        if constexpr (h == 4 && !W) { if (s > 0) bar_sync(BAR_SX, 256); }
                        if constexpr (h == 5) {
                            if constexpr (W && !P1) get();
                            wg_wait<0>();
                            if constexpr (!(W ? P1 : P0)) {
                                put(oth);
                                bar_arrive(W ? BAR_QK : BAR_QJ, 256);
                            } else {
#pragma unroll
                                for (int i = 0; i < 8; i++) u[i] = keep(pack2(acc[2 * i], acc[2 * i + 1]));
                            }
                            if constexpr (W && !P1) {
#pragma unroll
                                for (int i = 0; i < 8; i++) { acc[2 * i] = bf_lo(u[i]); acc[2 * i + 1] = bf_hi(u[i]); }
                            }
                        }
                        wg_fence();
                        static_for<0, 4>([&](auto K4) {
                            constexpr int k4 = K4.value, r = 16 * kb + 4 * k4;
                            const uint32_t* w = (h < 5) == W ? wq : wk;
#ifndef NOBULK
                            wgmma_rs32<xblk(5 * W + kb) / 16 + k4 * 2, ((W && !P1 ? h : h % 5) | k4) != 0>(acc, w[r], w[r + 1], w[r + 2], w[r + 3], xr_lo);
#endif
                            if constexpr (((W ? BM1 : BM0) >> h & 1) && ((BT == 2 && k4 == 1) || (BT == 3 && k4 < 3))) { wg_commit(); wg_wait<1>(); wg_fence(); }
                        });
                        wg_commit();
                        if constexpr (h == 7) {
                            if (s == 0) {
#pragma unroll 1
                                for (int i = 0; i < 3; i++) mbar_wait_long(sb + MB_F + 8 * (2 * W + i), 1);
#pragma unroll
                                for (int k = 0; k < AE; k++) lv(k);
                            }
                        }
                        if constexpr (!W && LAG == 2 * h + 1) bar_arrive(BAR_PUB, 256);
                        if constexpr (AP && h >= AP - 1 && h < AP + 1) { if constexpr (AQ == 0 || (AQ == 1 && W) || (AQ >= 3 && !W)) { lv(2 * (h - AP + 1)); lv(2 * (h - AP + 1) + 1); } }
                        if constexpr (h > 0 && h == (W ? P1 : P0)) {
                            stsm4t(st0 + oth, u[0], u[1], u[2], u[3]);
                            stsm4t(st0 + (oth + 2048), u[4], u[5], u[6], u[7]);
                            bar_arrive(W ? BAR_QK : BAR_QJ, 256);
                        }
                        if constexpr (W && P1 && h == G1) get();
                        if constexpr (h == GH && !W && GA) { gt = lds1(sb + OFF_TG); gs = lds1(sb + OFF_RL + 12 + (s > SW ? 16 : 0)); }
                        if constexpr (h == 9 && !W) {
                            get();
                            if (GA && warp < 2 && s > 0) {
                                if (s < NVC) mbar_wait_long(sb + MB_EN, s & 1);
                                const char* src = win + __shfl_sync(0xffffffffu, gs + 0x100000 + warp * 0x4000, 0);
                                gatev(gt + (warp ? H1 : H0));
                                asm volatile("{.reg .pred p; elect.sync _|p, 0xffffffff;\n"
                                             "@p cp.async.bulk.shared::cluster.global.mbarrier::complete_tx::bytes [%0], [%1], 3072, [%2];}"
                                             :: "r"(sb + OFF_MEMT + warp * 5120), "l"(src), "r"(sb + MB_G + 24 - warp * 16) : "memory");
                            }
                        }
                        if constexpr (BT == 4 && ((W ? BM1 : BM0) >> h & 1)) wg_wait<0>(); else if constexpr (h != 4 && h != 9) wg_wait<1>();
                        if constexpr (!W && LAG == 2 * h + 2) bar_arrive(BAR_PUB, 256);
                        if constexpr (h == 6 && !W) arrive_e(sb + MB_EL);
                        if constexpr (h == 7 && !W) arrive_e(sb + MB_EM);
                        if constexpr (h == 7) TSTAMP(9);
                        if constexpr (h == 0) TSTAMP(6);
                        if constexpr (h == 8 && !W) arrive_e(sb + MB_EN);
                    });
                    wg_wait<0>();
                    if constexpr (!W || P1) {
#pragma unroll
                        for (int i = 0; i < 8; i++) { acc[2 * i] += bf_lo(u[i]); acc[2 * i + 1] += bf_hi(u[i]); }
                    }
                    put(own);
#pragma unroll
                    for (int k = AP && ((AQ == 1 && !W) || (AQ == 3 && W)) ? 0 : AE; k < 4; k++) lv(k);
                };
                if (__builtin_expect(wg == 0, 1)) bulk(IC<0>()); else bulk(IC<1>());
                arrive_e(sb + MB_EA);
                if (AQ == 2) { bar_sync(BAR_PUB, 256); la(0); la(1); la(2); la(3); }
                TSTAMP(0);
            }
            uint32_t f[12][4];
            auto ld = [&](int n) { ldsm4t(st0 + (OFF_WO + n * 2048), f[n][0], f[n][1], f[n][2], f[n][3]); };
            {
                float qa[4] = {0, 0, 0, 0}, qb[4] = {0, 0, 0, 0}, ka[4] = {0, 0, 0, 0}, kb[4] = {0, 0, 0, 0}, cu[4] = {0, 0, 0, 0}, cv[4] = {0, 0, 0, 0};
                uint32_t b[10][4], u0, u1;
                auto grp = [&](int i) { if (wg) bar_sync(bar_g(i, 1), 160); else bar_sync(bar_g(i, 0), 160); };
                auto lb = [&](int j) { ldsm4t(lm + (OFF_MEMT + j * 512), b[j][0], b[j][1], b[j][2], b[j][3]); blk(warp); };
                auto mm = [&](float* c, const uint32_t* w, int k) { mma16(c, w[0], w[1], w[2], w[3], b[k >> 1][2 * (k & 1)], b[k >> 1][2 * (k & 1) + 1]); blk(warp); };
                auto mq = [&](int k) { mm(k & 1 ? qb : qa, wq + 4 * k, k); };
                auto mk = [&](int k) { mm(k & 1 ? kb : ka, wk + 4 * k, k); };
                auto mu = [&](int k) { mm(cu, a[k], k); };
                blk(warp);
                grp(0);
                lb(0); lb(1);
                mu(0); TSTAMP(1); mq(0); mk(0); mq(1); mu(1); mk(1); lb(2);
                mq(2); mk(2); mu(2); la(4); mq(3); mk(3); mu(3); lb(3); la(5);
                mq(4); mk(4); mq(5); mu(4); la(6); mk(5); mq(6); mu(5); lb(4); la(7);
                mk(6); mq(7); mu(6); lb(5); mk(7); mq(8); mq(9); mu(7);
                grp(1); TSTAMP(8); lb(6); lb(7); mk(8); mq(10); mk(9); mq(11);
                u0 = pack2(cu[0], cu[1]); u1 = pack2(cu[2], cu[3]); blk(warp);
                mq(12); mk(10); mq(13); mk(11);
                lb(8); lb(9);
                mq(14); mk(12); mq(15); mk(13); mq(16); mq(17); mk(14); mq(18); mq(19); mk(15); mk(16);
                stsm2t(st0 + OFF_Q0, pack2(qa[0] + qb[0], qa[1] + qb[1]), pack2(qa[2] + qb[2], qa[3] + qb[3]));
                bar_arrive(BAR_Q, 352);
                TS2(0);
                blk(warp);
                mk(17); mk(18);
#pragma unroll
                for (int k = 8; k < 8 + VE; k++) la(k);
                mk(19);
                stsm2t(st0 + OFF_K0, pack2(ka[0] + kb[0], ka[1] + kb[1]), pack2(ka[2] + kb[2], ka[3] + kb[3]));
                bar_arrive(BAR_K, 416);
                TSTAMP(2);
                auto rest = [&](auto TWO) {
                    constexpr bool T2 = TWO.value;
                    uint32_t g[12][4];
                    lm = keep(lm);
                    auto pre = [&](int n) { if (n < 4 || !T2) ld(n); else ldsm4t(lm + ub + (n - 4) * 512, g[n - 4][0], g[n - 4][1], g[n - 4][2], g[n - 4][3]); };
                    uint32_t l16, pw, sr, da, va;
                    blk(warp);
                    cv[0] = bf_lo(u0); cv[1] = bf_hi(u0); cv[2] = bf_lo(u1); cv[3] = bf_hi(u1);
#pragma unroll
                    for (int k = 8; k < 8 + VE; k++) mm(cv, a[k], k);
                    bar_sync(BAR_S, 288);
#pragma unroll
                    for (int k = 8 + VE; k < 8 + VE + VD; k++) la(k);
                    { const uint32_t o = lm; l16 = keep(sb + ((o >> 1) & 112) + (((o << 3) ^ o) & 128) + (o & 256)); blk(warp); }
#pragma unroll
                    for (int k = 8 + VE; k < (VL ? 20 - VD : 20); k++) {
                        mm(cv, a[k], k);
                        if (k + VD < 20) la(k + VD); else {
                            if (k + VD == 20 && s == 0) bar_sync(BAR_PUB, 288);
#pragma unroll
                            for (int n = (k + VD - 20) * W0 / VD; n < (k + VD - 19) * W0 / VD; n++) { pre(n); blk(warp); }
                        }
                        if (k == 11) { const uint32_t ln = (l16 >> 4) & 31; sr = keep(sb + OFF_SM + warp * 160 + min(ln, 19u) * 8); blk(warp); }
                        if (k == 12) { const uint32_t ln = (l16 >> 4) & 31, pb = warp * 32 + (ln & 3) * 8; pw = keep(sb + OFF_PM + selu(ln < 4, pb, 2 * pb + 252 + (ln & 28))); blk(warp); }
                        if (k == 14) {
                            const uint32_t o = l16 - sb, e = ((o >> 1) & 127) + ((o & 256) << 4);
                            da = keep(e ^ (xch_page(ta, 0) + head * 128 + (head & 7) * 16));
                            blk(warp);
                        }
                        if (k == 15) { va = keep((l16 >> 1) + (sb - (sb >> 1) + OFF_VM) + warp * 256); blk(warp); }
                    }
                    if (!VL) {
                        sts2(va, pack2(cv[0], cv[1]), pack2(cv[2], cv[3]));
                        bar_arrive(BAR_V, 384);
                        blk(warp);
                    }
                    bar_sync(BAR_SR, 288);
                    TSTAMP(4);
                    const float2 u = lds2f(sr), v = lds2f(sr + (OFF_SP - OFF_SM)), w = lds2f(sr + (OFF_SP + 1280 - OFF_SM));
                    blk(warp);
#pragma unroll
                    for (int k = 20 - VD; k < 20; k++) if (VL) mm(cv, a[k], k);
                    float x = u.x + v.x + w.x, y = u.y + v.y + w.y;
                    int m = __float_as_int(fmaxf(x, y));
                    m ^= (m >> 31) & 0x7fffffff;
                    blk(warp);
                    m = __reduce_max_sync(0xffffffffu, m);
                    if (VL) { sts2(va, pack2(cv[0], cv[1]), pack2(cv[2], cv[3])); bar_arrive(BAR_V, 384); }
#pragma unroll
                    for (int n = W0; n < W1; n++) pre(n);
                    m ^= (m >> 31) & 0x7fffffff;
                    const float mx = __int_as_float(m) * -SCL_B;
                    x = ex2(fmaf(x, SCL_B, mx)); y = ex2(fmaf(y, SCL_B, mx));
                    if (l16 < sb + 320) sts1(pw, pack2(x, y));
                    bar_arrive(BAR_PM, 384);
                    blk(warp);
                    const uint32_t tag = lds1(sb + OFF_EP) ^ s;
                    const uint32_t fx = __reduce_add_sync(0xffffffffu, l16 < sb + 320 ? __float_as_uint((x + y) + 8.f) - 0x41000000u : 0u);
                    const float fs = __uint2float_rn(fx);
                    blk(warp);
#pragma unroll
                    for (int n = W1; n < W2; n++) pre(n);
                    blk(warp);
                    sts1(sb + OFF_INV + warp * 4, bit0(__float_as_uint(rcpf(fs) * 1048576.f), tag + l16));
                    TSTAMP(5);
                    if (s == NSEG - 1) return true;
                    const uint32_t ia = keep(sb + OFF_INV + ((keep(l16) >> 1) & 24));
                    uint32_t bb[6][4];
                    float ca[4] = {0, 0, 0, 0}, cb[4] = {0, 0, 0, 0}, cd[4] = {0, 0, 0, 0}, ce[4] = {0, 0, 0, 0};
                    auto lo = [&](int j) { ldsm4t(lm + uo + ((j < 2 ? HALF + 1024 : 0) + j * 512), bb[j][0], bb[j][1], bb[j][2], bb[j][3]); blk(warp); };
                    auto lf = [&](int n) { if (T2 || n >= 7) { ld(n); blk(warp); } };
                    auto lg = [&](int n) { if (T2 && n < 12) { ldsm4t(lm + ub + n * 512, g[n][0], g[n][1], g[n][2], g[n][3]); blk(warp); } };
                    auto ma = [&](float* c, int n) { mma16(c, f[n][0], f[n][1], f[n][2], f[n][3], bb[n >> 1][2 * (n & 1)], bb[n >> 1][2 * (n & 1) + 1]); blk(warp); };
                    auto mb = [&](float* c, int n) { if (T2) { mma16(c, g[n][0], g[n][1], g[n][2], g[n][3], bb[n >> 1][2 * (n & 1)], bb[n >> 1][2 * (n & 1) + 1]); blk(warp); } };
                    blk(warp);
                    bar_sync(BAR_O, 384);
                    lo(0); lo(1);
#pragma unroll
                    for (int n = W2; n < 7; n++) { pre(n); blk(warp); }
                    ma(ca, 0); mb(cb, 0); ma(ca, 1); lg(3); mb(cb, 1); lf(4); lf(5); ma(ca, 2); lf(6); mb(cb, 2); lf(7); ma(ca, 3); lf(8);
                    const float2 inv = lds2f(ia);
                    auto st = [&](const float* c, const float* d, uint32_t o) {
                        st_pkt8(win + o, bit0(pack2((c[0] + d[0]) * inv.x, (c[1] + d[1]) * inv.y), __float_as_uint(inv.x)),
                                bit0(pack2((c[2] + d[2]) * inv.x, (c[3] + d[3]) * inv.y), __float_as_uint(inv.x)));
                        blk(warp);
                    };
                    mb(cb, 3);
                    bar_sync(BAR_OR, 288);
                    lo(2); lo(3);
                    ma(ca, 4); lo(4); ma(ca, 5); lf(9); ma(ca, 6); lo(5); ma(ca, 7); lf(10); ma(ca, 8); lf(11); ma(ca, 9); lg(4);
                    ma(cd, 10); ma(ca, 11); lg(5);
                    st(ca, cd, da);
                    bar_arrive(BAR_OF, 288);
                    TSTAMP(3);
                    if constexpr (T2) {
                        lg(6); lg(7);
                        mb(cb, 4); lg(8); mb(ce, 5); lg(9); mb(cb, 6); lg(10); mb(ce, 7); lg(11); mb(cb, 8); mb(ce, 9); mb(cb, 10); mb(ce, 11);
                        st(cb, ce, da ^ (xch_page(ta, 0) ^ xch_page(tb, 0)));
                    }
#pragma unroll
                    for (int k = 0; k < AE; k++) if (!AP) la(k);
                    return false;
                };
                if (two ? rest(IC<1>()) : rest(IC<0>())) break;
            }
            TSTAMP(7);
            if (WS) bar_sync(BAR_WO, 384); else bar_arrive(BAR_WO, 384);
        }
        TLC(0, 65);
        asm volatile("setmaxnreg.dec.sync.aligned.u32 168;");
        uint32_t f[24][4];
        uint32_t lnt; asm volatile("mov.u32 %0, %%laneid;" : "=r"(lnt));
        {
            const uint32_t sbb = sb + wo_b(two ? warp : 0) + ((lnt & 7) + ((lnt >> 4) << 3)) * 32 + (((lnt >> 3) ^ (lnt >> 2)) & 1) * 16;
#pragma unroll
            for (int n = 0; n < 12; n++) {
                ldsm4t(st0 + (OFF_WO + n * 2048), f[n][0], f[n][1], f[n][2], f[n][3]);
                ldsm4t(sbb + n * 512, f[12 + n][0], f[12 + n][1], f[12 + n][2], f[12 + n][3]);
            }
        }
        bar_sync(BAR_QK, 256);
        TLC(0, 67);
        const uint32_t ep = lds1(sb + OFF_EP);
        char* tp = reinterpret_cast<char*>(g_tail) + head * 40960;
        uint32_t ts = sb + OFF_WV + warp * 2048;
        const uint32_t o16 = lnt * 16;
#pragma unroll 1
        for (int t = 0; t < 4; t++) {
            const uint32_t b0 = ((SB0 + (t == 0 ? OFF_XR + 5120 : t == 1 ? OFF_OXE : t == 3 ? OFF_OXL : OFF_OX)) >> 4) | (1u << 16);
            const uint32_t b1 = ((SB0 + (t == 0 ? OFF_MEMT : t == 1 ? OFF_OXE + 4096 : OFF_OXG + (t - 2) * 8192)) >> 4) | (1u << 16);
            float acc[2][16];
#pragma unroll
            for (int i = 0; i < 16; i++) acc[0][i] = acc[1][i] = 0.f;
            auto st = [&](int i, uint32_t blkc) {
                const float* a = acc[i];
                sts4(ts + o16 + i * 1024, make_uint4((pack2(a[0], a[1]) & ~1u) | (ep & 1), pack2(a[2], a[3]), pack2(a[4], a[5]), pack2(a[6], a[7])));
                sts4(ts + o16 + i * 1024 + 512, make_uint4((pack2(a[8], a[9]) & ~1u) | (ep & 1), pack2(a[10], a[11]), pack2(a[12], a[13]), pack2(a[14], a[15])));
                asm volatile("fence.proxy.async.shared::cta;" ::: "memory");
                __syncwarp();
                asm volatile("{.reg .pred p; elect.sync _|p, 0xffffffff; @p cp.async.bulk.global.shared::cta.bulk_group [%0], [%1], 1024;}"
                             :: "l"(tp + blkc * 1024), "r"(ts + i * 1024) : "memory");
            };
            if (t < 2) mbar_wait(sb + MB_F + 16 + 8 * t, 0); else if (t == 2) bar_sync(BAR_WO, 384); else bar_sync(BAR_O, 384);
            wg_fence();
            static_for<0, 8>([&](auto N) {
                constexpr int i = N.value >> 2, k = N.value & 3;
                wgmma_rs32<k * 2, k != 0>(acc[i], f[12 * i + k][0], f[12 * i + k][1], f[12 * i + k][2], f[12 * i + k][3], b0);
            });
            wg_commit();
            mbar_wait(sb + MB_F + 8 * (t ^ 2), 0);
            static_for<0, 2>([&](auto I) {
                constexpr int i = I.value;
                wg_fence();
                static_for<4, 12>([&](auto K) {
                    constexpr int k = K.value;
                    wgmma_rs32<(k / 4 - 1) * 256 + (k & 3) * 2, 1>(acc[i], f[12 * i + k][0], f[12 * i + k][1], f[12 * i + k][2], f[12 * i + k][3], b1);
                });
                wg_commit();
            });
            wg_wait<1>();
            st(0, ta);
            wg_wait<0>();
            if (two) st(1, tb);
            if (t == TX0) bar_arrive(BAR_X, 384);
            TLC(0, t == 3 ? 76 : t == 1 ? 68 : 66);
            tp += 32 * 40960; ts += 16384;
        }
        asm volatile("cp.async.bulk.commit_group;" ::: "memory");
        gatev(clkv() + (warp >= 4 ? TD3 : TD2));
        tail_sum(sb, 2 + (warp >> 2), BAR_SR + (warp >> 2), out);
        TLC(0, 79); TLC(4, 78);
        asm volatile("cp.async.bulk.wait_group.read 0;" ::: "memory");
    } else if (warp < 12) {
        asm volatile("setmaxnreg.dec.sync.aligned.u32 48;");
        LANE_REGS;
        const int w4 = warp & 3;
        asm volatile("barrier.cluster.wait.acquire.aligned;" ::: "memory");
        const uint32_t wv_lo = ((SB0 + OFF_WV) >> 4) | (64u << 16);
        uint32_t vm0 = 0, vm1 = 0, vn0 = 0, vn1 = 0;
        (void)lane;
        auto load_wo = [&](int kb) {
            auto row = [&](uint32_t p) { return head * DH + (rank + p) % 3 * 64; };
            auto wa = [&](uint32_t w, uint32_t p) { tma2d_e(sb + OFF_WO + w * HALF + p * 8192, &tmWo, (w * 5 + rank) * 64, row(p), sb + MB_WO); };
            auto wb = [&](uint32_t j0, uint32_t j1) {
#pragma unroll 1
                for (uint32_t i = 3 * j0; i < 3 * j1; i++) tma2d_e(sb + wo_b(i / 3) + i % 3 * 2048, &tmWb, tile_b(i / 3 * 3 + rank) * 16, row(i % 3), sb + MB_WO);
            };
            if (kb == 0) { wa(0, 0); wa(0, 1); }
            if (kb == 2) { wa(0, 2); wb(0, 1); }
            if (kb == 4) { wa(1, 0); wb(1, 2); }
            if (kb == 6) { wa(1, 1); wa(1, 2); }
            if (kb == 8) wb(2, rank ? 5 : 6);
        };
        if (warp == 8) {
            const int e0 = head * DH + rank * 64;
            for (int i = PWIN; i < 5; i++) {
                mbar_wait(sb + MB_F + 8 * (i - PWIN), 0);
                expect_e(sb + MB_F + 8 * i, 32768);
                tma2d_e(sb + OFF_WV + i * 16384, &tmWq, e0, i * 128, sb + MB_F + 8 * i);
                tma2d_e(sb + OFF_WO + i * 16384, &tmWk, e0, i * 128, sb + MB_F + 8 * i);
            }
            for (int i = 0; i < 5; i++) {
                mbar_wait(sb + MB_E + 8 * i, 0);
                if (i + 5 - PWIN < 5) mbar_wait(sb + MB_F + 8 * (i + 5 - PWIN), 0);
                expect_e(sb + MB_F + 8 * i, 16384);
                tma2d_e(sb + OFF_WV + i * 16384, &tmWv, e0, i * 128, sb + MB_F + 8 * i);
                if (WI == 2) load_wo(2 * i);
            }
            if (WI == 1) for (int i = 0; i < 5; i++) load_wo(2 * i);
        }
        auto pvx = [&](int seg, const uint32_t m0, const uint32_t m1, uint32_t* o, auto sync) {
            const uint4* vq = g_vx + (blockIdx.x * 64 + seg) * 256 + w4 * 32 + ((keep(l16) - sb) >> 4);
            const uint4 u = ld_pkt(vq), v = ld_pkt(vq + 128);
            const uint32_t px_lo = ((SB0 + OFF_PX) >> 4) | (8u << 16);
            sync();
            const uint32_t b[12] = {m0, m1, 0, 0, u.x, u.y, u.z, u.w, v.x, v.y, v.z, v.w};
            uint32_t a[12], z;
            asm volatile("shr.u32 %0, %1, 8;" : "=r"(z) : "r"(seg + warp));
#pragma unroll
            for (int i = 0; i < 12; i++) asm volatile("xor.b32 %0, %1, %2;" : "=r"(a[i]) : "r"(b[i]), "r"(z));
            blk(warp);
            static_for<0, 2>([&](auto H) {
                constexpr int h = H.value;
                float acc[8] = {0, 0, 0, 0, 0, 0, 0, 0};
                wg_fence();
                wgmma_rs16<h * 80, 0>(acc, a[0], a[1], a[2], a[3], px_lo);
                wgmma_rs16<h * 80 + 8, 1>(acc, a[4], a[5], a[6], a[7], px_lo);
                if constexpr (h == 1) wgmma_rs16<h * 80 + 24, 1>(acc, a[8], a[9], a[10], a[11], px_lo);
                wg_commit();
                wg_wait<0>();
#pragma unroll
                for (int i = 0; i < 4; i++) o[4 * h + i] = keep(pack2(acc[2 * i], acc[2 * i + 1]));
                blk(warp);
            });
        };
        auto stage = [&](uint32_t dst, const uint32_t* o) {
            const uint32_t ln = (keep(l16) - sb) >> 4;
            const uint32_t sa = sb + dst + ((ln & 7) + ((ln >> 4) << 3)) * 128 + (((2 * w4 + ((ln >> 3) & 1)) ^ (ln & 7)) << 4);
            stsm4t(sa, o[0], o[1], o[2], o[3]);
            stsm4t(sa + 2048, o[4], o[5], o[6], o[7]);
            asm volatile("fence.proxy.async.shared::cta;" ::: "memory");
        };

        for (int s = 0; ; s++) {
            DBGBASE;
            if (s >= NVC && s < NSEG) { arrive_e(sb + MB_EL); arrive_e(sb + MB_EM); arrive_e(sb + MB_EN); arrive_e(sb + MB_EA); }
            float sc[10];
#pragma unroll
            for (int j = 0; j < 10; j++) sc[j] = 0.f;
            uint4 vu, vv;
            uint32_t o[8] = {0, 0, 0, 0, 0, 0, 0, 0}, w[5] = {0, 0, 0, 0, 0};
            if (s > 0) {
                asm volatile("fence.proxy.async.shared::cta;" ::: "memory");
                pvx(max(s - 2, 0), vn0, vn1, o, [&]() {
                    if (warp == 9) expect_e(sb + MB_SX, 5120);
                    if (warp == 10 && s < NSEG) mbar_wait(sb + MB_XA, s & 1);
                    const uint32_t qa_lo = ((SB0 + OFF_QX) >> 4) | (1u << 16), ka_lo = ((SB0 + OFF_K1) >> 4) | (1u << 16);
                    const uint32_t p1 = mapa(sb, (rank + 1) % 3) - sb, p2 = mapa(sb, (rank + 2) % 3) - sb;
                    const uint32_t sx = s == NSEG ? OFF_SXL : OFF_SX, lz = keep(l16);
                    const uint32_t xo = keep(lz + sx + w4 * 640), mo = keep(sb + w4 * 640 + ((lz - sb) >> 2) + sx + 512);
                    float d[20];
#pragma unroll
                    for (int j = 0; j < 20; j++) d[j] = 0.f;
                    blk(warp);
                    if (s < NSEG) bar_sync(BAR_WO, 384);
                    wg_fence();
                    static_for<0, 4>([&](auto K4) { wgmma_ss40<K4.value * 2, K4.value != 0>(d, qa_lo, ka_lo); });
                    wg_commit();
                    wg_wait<0>();
#pragma unroll
                    for (int j = 0; j < 5; j++) w[j] = pack2(d[4 * j], d[4 * j + 1]);
                    st_async4(p1 + xo + 2560, w[1], w[2], w[3], w[4], p1 + sb + MB_SX); st_async4(p2 + xo, w[1], w[2], w[3], w[4], p2 + sb + MB_SX);
                    st_async1(p1 + mo + 2560, w[0], p1 + sb + MB_SX);                   st_async1(p2 + mo, w[0], p2 + sb + MB_SX);
                    if (s < NSEG) { if (warp == 10) mbar_wait(sb + MB_XB, s & 1); bar_arrive(BAR_SX, 256); }
                    TSTAMP(6);
                    blk(warp);
                });
                TSTAMP(2);
            }
            if (s < NVC) {
                const uint32_t xr_lo = ((SB0 + OFF_XR) >> 4) | (1u << 16);
                float acc[16];
#pragma unroll
                for (int i = 0; i < 16; i++) acc[i] = 0.f;
                mbar_wait(sb + MB_XA, s & 1);
                mbar_wait(sb + MB_XB, s & 1);
                static_for<0, 10>([&](auto KB) {
                    constexpr int kb = KB.value;
                    if (!(kb & 1) && s == 0) {
                        mbar_wait(sb + MB_E + 4 * kb, 0);
                        mbar_wait(sb + MB_F + 4 * kb, 1);
                        if (warp == 8) {
                            if (WI == 0) load_wo(kb);
                            if (WI == 3 && kb == 6) { load_wo(0); load_wo(2); }
                            if (WI == 3 && kb == 8) { load_wo(4); load_wo(6); load_wo(8); }
                            if (WI == 4 && kb >= 4) load_wo(kb - 4);
                            if (WI == 4 && kb == 8) { load_wo(6); load_wo(8); }
                        }
                    }
                    wg_fence();
                    static_for<0, 4>([&](auto K4) {
                        constexpr int k4 = K4.value;
                        wgmma_ss32<(kb * 4 + k4) * 128, xblk(kb) / 16 + k4 * 2, (kb | k4) != 0>(acc, wv_lo, xr_lo);
                    });
                    wg_commit();
                    if constexpr (kb) wg_wait<1>();
                    if constexpr (kb == 3) { arrive_e(sb + MB_EL); arrive_e(sb + MB_EM); arrive_e(sb + MB_EN); }
                });
                wg_wait<0>();
                arrive_e(sb + MB_EA);
                uint4* vp = g_vx + (blockIdx.x * 64 + s) * 256 + w4 * 32 + ((keep(l16) - sb) >> 4);
                vp[0] = vu = make_uint4(pack2(acc[0], acc[1]), pack2(acc[2], acc[3]), pack2(acc[4], acc[5]), pack2(acc[6], acc[7]));
                vp[128] = vv = make_uint4(pack2(acc[8], acc[9]), pack2(acc[10], acc[11]), pack2(acc[12], acc[13]), pack2(acc[14], acc[15]));
            } else {
                const uint4* vq = g_vx + (blockIdx.x * 64 + min(s, NSEG - 1)) * 256 + w4 * 32 + ((keep(l16) - sb) >> 4);
                vu = ld_pkt(vq); vv = ld_pkt(vq + 128);
            }
            if (s > 0) {
                const uint32_t sx = s == NSEG ? OFF_SXL : OFF_SX, lz = keep(l16), xo = lz + sx + w4 * 640, mo = sb + w4 * 640 + ((lz - sb) >> 2) + sx + 512;
                if (!VP && (WD & 3) && s >= NVC && s < NSEG) mbar_wait(sb + ((WD & 3) == 1 ? MB_EN : MB_EA), s & 1);
                mbar_wait(sb + MB_SX, (s - 1) & 1);
                TSTAMP(0);
                const uint4 u = lds4(xo), v = lds4(xo + 2560);
                const uint32_t um = lds1(mo), vm = lds1(mo + 2560);
                const uint32_t h[5] = {badd2(um, vm), badd2(u.x, v.x), badd2(u.y, v.y), badd2(u.z, v.z), badd2(u.w, v.w)};
#pragma unroll
                for (int j = 0; j < 5; j++) { sc[2 * j] = bf_lo(h[j]) + bf_lo(w[j]); sc[2 * j + 1] = bf_hi(h[j]) + bf_hi(w[j]); }
                blk(warp);
                if ((WD & 4) && s >= NVC && s < NSEG) mbar_wait(sb + MB_EA, s & 1);
                bar_sync(BAR_P, 128);
                stage(OFF_OX, o);
                if (s == NSEG) bar_arrive(BAR_WO, 384);
                bar_sync(BAR_P, 128);
                if (warp == 9 && s > 1) {
                    if (s == NSEG) share_o(sb, rank, OFF_OX, 0);
                    else if (l16 == sb) {
                        tma_st(&tmOx, sb + OFF_OX, blockIdx.x * 64, (s - 2) * 32);
                        asm volatile("cp.async.bulk.commit_group;" ::: "memory");
                        if (prog_step(s)) asm volatile("cp.async.bulk.wait_group 0;" ::: "memory");
                        else asm volatile("cp.async.bulk.wait_group.read 0;" ::: "memory");
                    }
                    __syncwarp();
                }
            }
            TSTAMP(8);
            auto softmax = [&]() {
                const uint32_t lz = keep(l16), o16 = lz - sb;
                const int lim = 8 + 8 * w4 + (o16 >> 6) - ((o16 >> 3) & 6);
#pragma unroll
                for (int j = 2; j < 10; j++) if (8 * (j >> 1) + (j & 1) > lim) sc[j] = -3.0e38f;
                float mx = fmaxf(fmaxf(fmaxf(fmaxf(sc[2], sc[3]), fmaxf(sc[4], sc[5])), fmaxf(fmaxf(sc[6], sc[7]), fmaxf(sc[8], sc[9]))), fmaxf(sc[0], sc[1]));
                mx = fmaxf(mx, __shfl_xor_sync(0xffffffffu, mx, 1));
                mx = fmaxf(mx, __shfl_xor_sync(0xffffffffu, mx, 2));
                mx *= -SCL_B;
                float sum = 0.f;
#pragma unroll
                for (int j = 0; j < 10; j++) { sc[j] = ex2(fmaf(sc[j], SCL_B, mx)); sum += sc[j]; }
                sum += __shfl_xor_sync(0xffffffffu, sum, 1);
                sum += __shfl_xor_sync(0xffffffffu, sum, 2);
                const float inv = rcpf(sum);
                stsm4(lz + (OFF_PX + 128) + w4 * 640, pack2(sc[2] * inv, sc[3] * inv), pack2(sc[4] * inv, sc[5] * inv), pack2(sc[6] * inv, sc[7] * inv), pack2(sc[8] * inv, sc[9] * inv));
                sts1(sb + OFF_PX + w4 * 640 + ((lz - sb) >> 2), pack2(sc[0] * inv, sc[1] * inv));
            };
            if (s == NSEG) {
                uint32_t o[8];
                pvx(s - 1, vm0, vm1, o, [&]() {
                    softmax();
                    asm volatile("fence.proxy.async.shared::cta;" ::: "memory");
                    blk(warp);
                    bar_sync(BAR_P, 128);
                });
                stage(OFF_OXL, o);
                bar_arrive(BAR_O, 384);
                bar_sync(BAR_P, 128);
                if (warp == 9) share_o(sb, rank, OFF_OXL, 1);
                TLC(10, s);
                break;
            }
            TLC(10, s);
            if (!SD) bar_arrive(BAR_K, 416);
            if (SD) bar_sync(BAR_K, 416);
            softmax();
            TSTAMP(7);
            TSTAMP(1);
            {
                uint32_t pm; asm volatile("shr.u32 %0, %1, 1;" : "=r"(pm) : "r"(l16 + sb));
                const uint32_t va = pm + OFF_VM + w4 * 256;
                const uint32_t o8 = pm - sb, oo = keep(sb + OFF_Q1 + w4 * 256 + (o8 & 56) * 4 + (((o8 >> 2) ^ (o8 >> 1)) & 16));
                const uint32_t p1 = mapa(sb, (rank + 1) % 3), p2 = mapa(sb, (rank + 2) % 3), o4 = (o8 & 224) + ((o8 >> 3) & 16) + ((o8 >> 1) & 12) + w4 * 256;
                const uint32_t r1 = keep(p1 + o4 + OFF_K0), r2 = keep(p2 + o4 + OFF_Q0), r3 = keep(r1 ^ 16), r4 = keep(r2 ^ 16);
                if (warp == 11 && s < NSEG - 1) expect_e(sb + MB_O, 2048);
                bar_sync(BAR_V, 384);
                const float2 v0 = lds2f(va), v1 = lds2f(va + 1024);
                vn0 = vm0; vn1 = vm1;
                vm0 = badd2(__float_as_uint(v0.x), __float_as_uint(v1.x)); vm1 = badd2(__float_as_uint(v0.y), __float_as_uint(v1.y));
                TSTAMP(3);
                if (s == NSEG - 1) {
                    bar_sync(BAR_PM, 384);
                    if (warp == 8) {
                        asm volatile("fence.proxy.async;" ::: "memory");
                        expect_e(sb + MB_F + 24, 12288);
#pragma unroll 1
                        for (uint32_t i = 0; i < 3; i++)
                            tma2d_e(sb + OFF_OXE + i * 4096, &tmOx, (head * 3 + (rank + i) % 3) * 64, (NSEG - 3) * 32, sb + MB_F + 24);
                    }
                } else {
                const uint32_t m1 = keep(p1 + MB_O), m2 = keep(p2 + MB_O);
                blk(warp);
                bar_sync(BAR_PM, 384);
                const uint4 qq = lds4(l16 + OFF_PM + 256);
                const uint32_t q0 = lds1(pm + OFF_PM);
                float oa[4] = {0, 0, 0, 0}, ob[4] = {0, 0, 0, 0}, oc[4] = {0, 0, 0, 0};
                blk(warp);
                mma16(oa, vu.x, vu.y, vu.z, vu.w, qq.x, qq.y);
                TSTAMP(4);
                mma16(ob, vv.x, vv.y, vv.z, vv.w, qq.z, qq.w);
                mma8(oc, vm0, vm1, q0);
                blk(warp);
                const uint32_t o0 = pack2((oa[0] + ob[0]) + oc[0], (oa[1] + ob[1]) + oc[1]), o1 = pack2((oa[2] + ob[2]) + oc[2], (oa[3] + ob[3]) + oc[3]);
                st_async1(r1, o0, m1); st_async1(r2, o0, m2);
                st_async1(r3, o1, m1); st_async1(r4, o1, m2);
                stsm2(oo, o0, o1);
                bar_arrive(BAR_O, 384);
                TSTAMP(5);
                bar_arrive(BAR_X, 160);
                if (warp == 11) { mbar_wait(sb + MB_O, s & 1); bar_arrive(BAR_OR, 288); }
                if (warp == 8 && s + 1 >= NVC) {
                    if (PFX == 1) asm volatile("prefetch.global.L2 [%0];" :: "l"(g_vx + (blockIdx.x * 64 + s + 1) * 256 + ((keep(l16) - sb) >> 1)));
                    if (PFX == 2) asm volatile("{.reg .pred p; elect.sync _|p, 0xffffffff; @p cp.async.bulk.prefetch.L2.global [%0], 4096;}" :: "l"(g_vx + (blockIdx.x * 64 + s + 1) * 256) : "memory");
                }
                if (warp == 9 && l16 < sb + 64 && blockIdx.x < 80 && s < NSEG - PD)
                    asm volatile("prefetch.global.L2 [%0];" :: "l"(xin + (s + PD) * 40960 + blockIdx.x * 512 + (keep(l16) - sb) * 8));
                }
            }
        }
    } else {
        asm volatile("setmaxnreg.dec.sync.aligned.u32 48;");
        LANE_REGS;
        const int g = warp & 3;
        sts1(sb + OFF_EP, ep0 + 1);
        if ((g & 1) && lane == 0) asm volatile("st.relaxed.gpu.global.b32 [%0], %1;" :: "l"(pp + (g >> 1) * 4096), "r"(0) : "memory");
        {
            uint4 v[5];
#pragma unroll
            for (int i = 0; i < 5; i++) {
                const unsigned short* m = reinterpret_cast<const unsigned short*>(mem0) + g * 160 + lane + 32 * i;
                v[i].x = m[0] | ((uint32_t)m[DM] << 16);          v[i].y = m[2 * DM] | ((uint32_t)m[3 * DM] << 16);
                v[i].z = m[4 * DM] | ((uint32_t)m[5 * DM] << 16); v[i].w = m[6 * DM] | ((uint32_t)m[7 * DM] << 16);
            }
            asm volatile("barrier.cluster.wait.acquire.aligned;" ::: "memory");
            mbar_wait_long(sb + MB_EN, 0);
#pragma unroll
            for (int i = 0; i < 5; i++) sts4(sb + OFF_MEMT + g * 2560 + 512 * i + ((lane & 7) + ((lane >> 4) << 3)) * 32 + (((lane >> 3) ^ (lane >> 2)) & 1) * 16, v[i]);
            bar_sync(BAR_R, 128);
        }
        auto refill = [&](int seg) {
#ifdef NOXA
            expect_e(sb + MB_XA, 2 * 4096);
#else
            expect_e(sb + MB_XA, 9 * 4096);
            asm volatile("{.reg .pred p; elect.sync _|p, 0xffffffff;\n"
                         "@p cp.async.bulk.tensor.3d.shared::cluster.global.mbarrier::complete_tx::bytes [%0], [%1, {0, %3, 3}], [%2];}"
                         :: "r"(sb + OFF_XR), "l"(&tmX7), "r"(sb + MB_XA), "r"(seg * 32) : "memory");
#endif
        };
        uint32_t hph = 0;
        const uint32_t gj = g == 3 ? 0 : g == 1 ? 10 : g == 2 ? 6 : 16, gn = g & 1 ? 3072 : 2048, gb = (0xce09u | 0xd0u) >> 4 * g & 15;
        static_assert(bar_g(1, 1) == 9 && bar_g(0, 1) == 13 && bar_g(1, 0) == 14 && bar_g(0, 0) == 12, "barriers");
        if (g == 3) bar_arrive(bar_g(0, 0), 160); else if (g == 1) bar_arrive(bar_g(0, 1), 160); else if (g == 2) bar_arrive(bar_g(1, 0), 160); else bar_arrive(bar_g(1, 1), 160);

        for (int s = 0; ; s++) {
            DBGBASE;
            uint32_t lz = l16 + lds1(sb + OFF_ZERO), o16 = lz - sb;
            uint32_t c0 = 0, t0 = 0;
            if (g == 2) {
                if (s < SW) {
                    if (s == 0) { mbar_wait(sb + MB_EA, 0); refill(1); }
                    if (s == SW - 1 && o16 == 0) {
                        const uint32_t t0 = lds1(sb + OFF_PRB), t1 = lds1(sb + OFF_PRB + 4), nr = lds1(sb + OFF_EP) * 2 + (HOME && t1 < t0);
                        asm volatile("st.relaxed.gpu.global.v4.b32 [%0], {%1,%1,%1,%1}; st.relaxed.gpu.global.v4.b32 [%0 + 16], {%1,%1,%1,%1};"
                                     :: "l"(g_near + blockIdx.x * 8), "r"(nr) : "memory");
                    }
                    __syncwarp();
                }
                uint32_t cal = keep(lz - l16) - clkv() * 9;
#pragma unroll
                for (int i = 0; i < 8; i++) cal = keep(cal + gtime() * 4);
                cal -= clkv() * 9;
                const char* wc = keepp(win + (XCH_CLK + ((o16 & 128) << 5) + ((o16 >> 2) & 28)) + head * 32);
                TS2(0);
                mbar_wait_long(sb + MB_S, s & 1);
                bar_arrive(BAR_SR, 288);
                TS2(1);
                c0 = clkv(); t0 = ((cal + c0 * 18) & ~31u) | ((s + 1) & 31);
                if (o16 < 256 && rank == 0 && s < NSEG - 1) st_pkt4(wc, t0);
            } else {
                mbar_wait(sb + MB_EA, s & 1);
                const uint32_t ln = o16 >> 4, r7 = sb + (ln & 7) * 128;
                const uint32_t lo = keep(r7 + (((ln >> 3) ^ (ln & 7)) << 4) + OFF_K1), lo2 = keep(lo ^ 64);
                const uint32_t lq = keep(r7 + (ln & 8) * (HALF / 8) + (((ln >> 4) ^ (ln & 7)) << 4) + OFF_Q0);
                const uint32_t so = keep(OFF_SM + (ln >> 2) * 160 + (ln & 3) * 8 + (g == 1 ? 0 : g == 0 ? 32 : 96));
                const uint32_t p1 = mapa(sb, (rank + 1) % 3), p2 = mapa(sb, (rank + 2) % 3);
                auto send = [&](float x, float y, uint32_t o) {
                    st_async2(p1 + so + (OFF_SP - OFF_SM + o), __float_as_uint(x), __float_as_uint(y), p1 + MB_S);
                    st_async2(p2 + so + (OFF_SP + 1280 - OFF_SM + o), __float_as_uint(x), __float_as_uint(y), p2 + MB_S);
                    sts2(sb + so + o, __float_as_uint(x), __float_as_uint(y));
                };
                uint32_t a[4][4], b[4][4];
                auto lda = [&]() {
                    const uint32_t lq1 = keep(lq ^ 32), lq2 = keep(lq ^ 64), lq3 = keep(lq ^ 96);
                    TS2(0);
                    blk(warp);
                    bar_sync(BAR_Q, 352);
                    ldsm4(lq, a[0][0], a[0][1], a[0][2], a[0][3]);
                    ldsm4(lq1, a[1][0], a[1][1], a[1][2], a[1][3]);
                    ldsm4(lq2, a[2][0], a[2][1], a[2][2], a[2][3]);
                    ldsm4(lq3, a[3][0], a[3][1], a[3][2], a[3][3]);
                    blk(warp);
                };
                auto ldb = [&](uint32_t o, uint32_t d) {
                    ldsm4(lo + o, b[0][0], b[0][1], b[0][2], b[0][3]);
                    ldsm4(lo + o + d, b[1][0], b[1][1], b[1][2], b[1][3]);
                    ldsm4(lo2 + o, b[2][0], b[2][1], b[2][2], b[2][3]);
                    ldsm4(lo2 + o + d, b[3][0], b[3][1], b[3][2], b[3][3]);
                };
                if (g == 1) {
                    lda();
                    bar_sync(BAR_K, 416);
                    ldb(0, -HALF);
                    bar_arrive(BAR_S, 288);
                    blk(warp);
                    float d0[4] = {0, 0, 0, 0}, d1[4] = {0, 0, 0, 0}, d2[4] = {0, 0, 0, 0}, d3[4] = {0, 0, 0, 0};
#pragma unroll
                    for (int i = 0; i < 4; i++) b[0][i] = badd2(b[0][i], b[1][i]);
                    mma16(d0, a[0][0], a[0][1], a[0][2], a[0][3], b[0][0], b[0][1]);
                    TS2(3);
                    mma16(d1, a[1][0], a[1][1], a[1][2], a[1][3], b[0][2], b[0][3]);
                    blk(warp);
#pragma unroll
                    for (int i = 0; i < 4; i++) b[2][i] = badd2(b[2][i], b[3][i]);
                    mma16(d2, a[2][0], a[2][1], a[2][2], a[2][3], b[2][0], b[2][1]);
                    mma16(d3, a[3][0], a[3][1], a[3][2], a[3][3], b[2][2], b[2][3]);
                    blk(warp);
                    send(((d0[0] + d0[2]) + (d1[0] + d1[2])) + ((d2[0] + d2[2]) + (d3[0] + d3[2])),
                         ((d0[1] + d0[3]) + (d1[1] + d1[3])) + ((d2[1] + d2[3]) + (d3[1] + d3[3])), 0);
                    TS2(5);
                    stsm4(lo, b[0][0], b[0][1], b[0][2], b[0][3]);
                    stsm4(lo2, b[2][0], b[2][1], b[2][2], b[2][3]);
                    expect_e(sb + MB_S, 512);
                } else {
                    ldb(1024 + (g >> 1) * 2048, 1024);
                    lda();
                    float d0[4] = {0, 0, 0, 0}, d1[4] = {0, 0, 0, 0};
#pragma unroll
                    for (int k = 0; k < 4; k++) {
                        mma16(d0, a[k][0], a[k][1], a[k][2], a[k][3], b[k & 2][2 * (k & 1)], b[k & 2][2 * (k & 1) + 1]);
                        if (k == 0) TS2(1);
                        mma16(d1, a[k][0], a[k][1], a[k][2], a[k][3], b[(k & 2) + 1][2 * (k & 1)], b[(k & 2) + 1][2 * (k & 1) + 1]);
                        blk(warp);
                    }
                    send(d0[0] + d0[2], d0[1] + d0[3], 0);
                    send(d1[0] + d1[2], d1[1] + d1[3], 32);
                    TS2(2);
                    __syncwarp();
                    expect_e(sb + MB_S, 1024);
                }
                TSTAMP(7);
            }
            if (s < SW) {
            if (s == 0 && g == 0) { TLC(12, 73); mbar_wait_long(sb + MB_WO, 0); TLC(12, 74); bar_arrive(BAR_PUB, 288); }
            o16 = l16 + lds1(sb + OFF_ZERO) - sb;
            if (s == SW - 2 && (g & 1)) {
                if (o16 == 0) {
                    uint32_t t = ~0u;
#pragma unroll 1
                    for (int i = 0; i < NPROBE; i++) {
                        const uint32_t c0 = clk32();
                        uint32_t c1 = c0 - 1;
                        asm volatile("{.reg .pred p; .reg .b32 x; atom.relaxed.gpu.global.exch.b32 x, [%1], %2; setp.le.u32 p, x, %2; @p mov.u32 %0, %%clock;}"
                                     : "+r"(c1) : "l"(win + (0x140000 + (blockIdx.x & 63) * 64 + (blockIdx.x >> 6) * 0x4000 + (g >> 1) * 4096 + o16)), "r"(i) : "memory");
                        t = min(t, c1 - c0);
                    }
                    sts1(sb + OFF_PRB + (g >> 1) * 4, t);
                }
                __syncwarp();
            }
            if (s == SW - 1 && g == 0) {
                uint32_t a0, a1, a2;
                const uint32_t ep = lds1(sb + OFF_EP);
#pragma unroll 1
                for (int c = 0; c < SPIN_LIM; c++) {
                    a0 = ld_relaxed(g_near + o16 / 2); a1 = ld_relaxed(g_near + 256 + o16 / 2); a2 = ld_relaxed(g_near + 512 + o16 / 2);
                    if (__all_sync(0xffffffffu, ((a0 ^ ep * 2) | (a1 ^ ep * 2) | (a2 ^ ep * 2)) < 2)) break;
                    __nanosleep(100);
                }
                const uint32_t b0 = __ballot_sync(0xffffffffu, a0 & 1), b1 = __ballot_sync(0xffffffffu, a1 & 1), b2 = __ballot_sync(0xffffffffu, a2 & 1);
                const uint32_t cw = blockIdx.x >> 5, bm = cw == 0 ? b0 : cw == 1 ? b1 : b2;
                const uint32_t side = (bm >> (blockIdx.x & 31)) & 1;
                const int n1 = __popc(b0) + __popc(b1) + __popc(b2);
                const int r1 = __popc(bm & ((1u << (blockIdx.x & 31)) - 1)) + (cw > 0 ? __popc(b0) : 0) + (cw > 1 ? __popc(b1) : 0);
                const int rk = side ? r1 : blockIdx.x - r1, no = side ? 96 - n1 : n1;
                const uint32_t next = side << 8 | (rk < 40 ? 2 * rk + side : min(2 * (no + rk - 40) + (side ^ 1), 95));
                TVAL0(5, next);
                if (g == 0) { sts1(sb + OFF_KP + 4, pause_at(next & 255)); sts4(sb + OFF_RL + 16, role_tab(next & 255, side)); }
            }
            }
            lz = l16 + lds1(sb + OFF_ZERO); o16 = lz - sb;
            const uint4 rl = lds4(sb + OFF_RL + (s >= SW ? 16 : 0));
            const uint32_t tag = keep((s ^ lds1(sb + OFF_EP)) & 1), dly1 = __shfl_sync(0xffffffffu, rl.z, 0);
            const char *mb = win + __shfl_sync(0xffffffffu, rl.w + 0x100000 + (0x0213 >> 4 * g & 3) * 0x4000, 0), *rp = win + __shfl_sync(0xffffffffu, rl.x, 0);
            const char* wp = keepp(win + ((rl.y ^ ((o16 >> 3) & 16)) + g * 32 + ((o16 >> 5) & 8) + ((o16 >> 4) & 4) + ((o16 & 16) << 8)));
            const uint32_t ra = keep(sb + (o16 & 256 ? OFF_R1 : OFF_R0) + (o16 & 240) * 8 + (o16 & 112) + ((o16 >> 5) & 12));
            const uint32_t ga = keep(sb + OFF_MEMT + gj * 512 + 2 * o16 + ((o16 >> 4) & 28)), gc = keep(ga + gn - 1024), gd = g == 3 ? H0 : g == 1 ? H1 : g == 2 ? H2 : H3;
            if (s < NSEG - 1) expect_e(sb + MB_G + 8 * g, gn);
            int cnt;
            if (g == 2) {
                if (s == NSEG - 1) break;
                const char* cp = keepp(mb + (XCH_CLK - 0x108000 + 2 * o16));
                gatev(c0 + DLYN);
                int late;
#pragma unroll 1
                for (cnt = 64; ; cnt--) {
                    late = ld_relaxed(cp) - t0;
                    if (!__any_sync(0xffffffffu, late & 31) || cnt == 0) break;
                }
                late = min(__reduce_max_sync(0xffffffffu, late), 64000);
                sts1(sb + OFF_TG, c0 + (late * 57 >> 10));
                TVAL(4, 64 - cnt);
#ifndef VLAT
                if (cnt < 64) EVT(3);
#endif
            } else {
                if (g == 1 && s < NSEG - 1) {
                    gatev(clkv() + HS);
                    asm volatile("fence.proxy.async.shared::cta;" ::: "memory");
                    tma2d_e(sb + OFF_MEMT, &tmX, 0, (s + 1) * 32, sb + MB_XA);
                    tma2d_e(sb + OFF_MEMT + 4096, &tmX, 64, (s + 1) * 32, sb + MB_XA);
                }
                if (g == 1 && s == NSEG - 1) {
                    asm volatile("fence.proxy.async;" ::: "memory");
                    expect_e(sb + MB_F + 16, 12288);
#pragma unroll 1
                    for (uint32_t i = 0; i < 3; i++)
                        tma2d_e(sb + (i ? OFF_MEMT - 4096 + i * 4096 : OFF_XR + 5120), &tmOx, (head * 3 + (rank + i) % 3) * 64, (NSEG - 4) * 32, sb + MB_F + 16);
                }
                if (g == 1 && prog_step(s) && s < NSEG - 2 && o16 == 0) st_release(g_prog + blockIdx.x, lds1(sb + OFF_EP) * 128 + s - 1);
                __syncwarp();
                if (s == NSEG - 1) break;
#ifndef PROF
                if (g == 0 && (((s & 7) == 6 && s < NSEG - 2) || s == NVC - 2)) {
                    const uint32_t* fv = g_flagv + blockIdx.x * 64 + s + 2;
                    const uint32_t e = lds1(sb + OFF_EP);
                    for (int c = 0; c < SPIN_LIM && ld_acquire(fv) != e; c++) { }
                }
#endif
                if (g == 1) {
                    bar_sync(BAR_X, 160);
                    asm volatile("fence.proxy.async.shared::cta;" ::: "memory");
                    expect_e(sb + MB_XB, 4096);
                    tma2d_e(sb + OFF_MEMT + 8192, &tmX, 128, (s + 1) * 32, sb + MB_XB);
                } else if (g == 3) {
                    if (dly1) expect_e(sb + MB_H, 4096);
                    bar_sync(BAR_OF, 288);
                    sts1(sb + OFF_SP + (o16 >> 2), 0x3f803f80);
                    asm volatile("fence.proxy.async.shared::cta;" ::: "memory");
                }
            }
            bar_sync(BAR_R, 128);
            const uint32_t tg = lds1(sb + OFF_TG);
            TS3(0);
            auto fetch = [&]() {
                asm volatile("{.reg .pred p; elect.sync _|p, 0xffffffff;\n"
                             "@p cp.async.bulk.shared::cluster.global.mbarrier::complete_tx::bytes [%0], [%1], %2, [%3];}"
                             :: "r"(sb + OFF_MEMT + gj * 512), "l"(mb), "r"(gn), "r"(sb + MB_G + 8 * g) : "memory");
            };
            if (dly1) {
                const uint32_t d_lo = SB0 >> 4;
                const uint32_t r1 = keep(ra ^ 32), r2 = keep(ra ^ 64), r3 = keep(ra ^ 96);
                if (g == 3) gatev(tg + dly1);
#pragma unroll 1
                for (cnt = 4 * WAIT_LIM; ; cnt--) {
                    if (g == 3)
                        asm volatile("{.reg .pred p; elect.sync _|p, 0xffffffff;\n"
                                     "@p cp.async.bulk.shared::cluster.global.mbarrier::complete_tx::bytes [%0], [%2], 2048, [%4];\n"
                                     "@p cp.async.bulk.shared::cluster.global.mbarrier::complete_tx::bytes [%1], [%3], 2048, [%4];}"
                                     :: "r"(sb + OFF_R0), "r"(sb + OFF_R1), "l"(rp), "l"(rp + 2048), "r"(sb + MB_H) : "memory");
                    TS3(1);
                    mbar_wait_long(sb + MB_H, hph);
#ifdef H1S
                    const uint32_t h0 = clkv();
#endif
                    const uint32_t w0 = lds1(ra), w1 = NT > 2 ? lds1(r1) : w0, w2 = NT > 1 ? lds1(r2) : w0, w3 = NT > 2 ? lds1(r3) : w2;
                    float d[4] = {0, 0, 0, 0};
                    wg_fence();
                    wgmma_ss8<OFF_R0 / 16, OFF_SP / 16, 0>(d, d_lo | (64u << 16), d_lo);
                    wgmma_ss8<OFF_R1 / 16, OFF_SP / 16, 1>(d, d_lo | (64u << 16), d_lo);
                    wg_commit();
                    sched();
                    uint32_t tv; asm volatile("{.reg .pred p; setp.ne.u32 p, %1, 0; vote.sync.ballot.b32 %0, p, 0xffffffff;}" : "=r"(tv) : "r"(tag) : "memory");
                    const bool stale = any_bit0(tagx(w0, w1, tv), tagx(w2, w3, tv)) && cnt;
#ifdef H1S
                    const uint32_t h1 = clkv() + stale;
#endif
                    wg_wait<0>();
#ifdef H1S
                    const uint32_t h2 = clkv();
#endif
                    const uint32_t tr = __float_as_uint(d[0]) >> 16;
                    const uint32_t pk = __byte_perm(tr + ((tr ^ tag) & 1), pack2(0.f, d[2]), 0x7610);
                    hph ^= 1;
                    asm volatile("{.reg .pred p; setp.eq.u32 p, %2, 0; @p st.relaxed.gpu.global.b32 [%0], %1;}" :: "l"(wp), "r"(pk), "r"((uint32_t)stale) : "memory");
#ifdef H1S
                    TVAL(0, h0); TVAL(7, h1); TVAL(4, h2);
#endif
                    if (!stale) break;
                    if (g == 3) expect_e(sb + MB_H, 4096);
                    bar_sync(BAR_R, 128);
                    EVT(0);
                }
                TS3(2);
                TVAL(8, 4 * WAIT_LIM - cnt);
            }
#ifdef PRB
            if (!dly1 && s == g_s0 && g == PRB) {
                uint32_t z = 0, t = 0;
                uint32_t ln = (ga >> 5) & 31;
#pragma unroll
                for (int i = 0; i < 32; i++) {
#if PRK == 0
                    z = lds1(sb + OFF_ZERO + z);
#elif PRK == 1
                    z = __shfl_xor_sync(0xffffffffu, z, 1);
#else
                    for (int k = 0; k < 8; k++) asm volatile("lop3.b32 %0, %0, %1, %1, 0x80;" : "+r"(z) : "r"(ln));
#endif
                    asm volatile("{.reg .pred p; .reg .b32 u; add.u32 u, %1, %3; setp.eq.u32 p, u, %2; @p mov.u32 %0, %%clock;}" : "+r"(t) : "r"(z), "r"(ln), "n"(0) , "r"(0));
                    asm volatile("" ::: "memory");
                    ln -= 1;
                }
                g_dbg[blockIdx.x * 512 + 256 + ((ga >> 5) & 31)] = t;
            }
#endif
            if (!GA || !(g & 1)) {
                mbar_wait(sb + (g == 3 ? MB_EL : g ? MB_EM : MB_EN), (s + 1) & 1);
                TS3(3);
                gatev(tg + gd);
                TS3(5);
                fetch();
            }
            if (XE && g == XE - 1 && s < NSEG - 2) { mbar_wait(sb + MB_EA, (s + 1) & 1); gatev(tg + gd + STG2); refill(s + 2); }
#pragma unroll 1
            for (cnt = 4 * WAIT_LIM; ; cnt--) {
                mbar_wait_long(sb + MB_G + 8 * g, s & 1);
#ifdef H1S
                TSTAMP(3);
#endif
                const uint32_t q0 = lds1(ga), q1 = lds1(ga + 1024), q2 = lds1(gc), b0 = tagx(q0, q1, tag), b1 = q2 ^ tag;
                if (!stale_or_arrive<160>(b0, b1, gb)) break;
                if (cnt == 0) { bar_arrive(gb, 160); break; }
                EVT(1 + (g & 1));
                arrive_e(sb + MB_G + 8 * g);
                expect_e(sb + MB_G + 8 * g, gn);
                fetch();
            }
            TSTAMP(6);
            TVAL(9, 4 * WAIT_LIM - cnt);
        }
        if (g == 1) { expect_e(sb + MB_F, 8192); expect_e(sb + MB_F + 8, 8192); }
        if (EPC && g == 0 && blockIdx.x == 0 && l16 == sb) g_epoch = lds1(sb + OFF_EP);
        asm volatile("setmaxnreg.inc.sync.aligned.u32 80;");
        bar_sync(BAR_X, 384);
        const uint32_t tx = clk32();
        gatev(tx + TD0);
        tail_sum(sb, 0, BAR_R, out);
        TLC(12, 77);
        gatev(tx + TD1);
        tail_sum(sb, 1, BAR_R, out);
        TLC(12, 75);
    }
    asm volatile("barrier.cluster.arrive.release.aligned;" ::: "memory");
    asm volatile("barrier.cluster.wait.acquire.aligned;" ::: "memory");
#if defined(DEV) || defined(TL)
    {
        uint32_t u, c, b;
        asm volatile("mov.u32 %0, %%tid.x; mov.u32 %1, %%ctaid.x; mov.u32 %2, %%dynamic_smem_size;" : "=r"(u), "=r"(c), "=r"(b));
        b += sb - CHAIN_SMEM + OFF_DBG;
#ifdef DEV
        if (u < 160) g_dbg[c * 512 + u] = lds1(b + u * 4);
#else
        if (u < 80) { g_tl[c * 80 + u] = lds1(b + u * 8); g_tc[c * 80 + u] = lds1(b + u * 8 + 4); }
#endif
    }
#endif
}

constexpr int NSIDE = 36, SST = 3, MAXJ = 32, NKS = 7;
constexpr uint32_t S_STAGE = 49152, S_STG = SST * S_STAGE, S_RST = S_STG + 65536, S_BAR = S_RST + 8192, SIDE_SMEM = S_BAR + 256;
constexpr uint32_t SB_FULL = S_BAR, SB_EMPTY = S_BAR + 64, SB_STAGED = S_BAR + 32, SB_FREE = S_BAR + 48;
enum { JV = 0, JQ = 1, JP = 2, JO = 3, JR = 4, JEND = 5, JS = 6 };
struct SideParams {
    CUtensorMap a[4], b[4], c[4], st[2], sto;
};
struct Job { uint32_t x, y; };
struct JobTable { Job j[NSIDE][MAXJ]; };
static_assert(OFF_OX % 1024 == 0 && OFF_QX % 1024 == 0 && OFF_MEMT % 1024 == 0, "swizzled tiles");
__constant__ const JobTable c_jobs = {{
    {{0x8020, 0xa0010}, {0x9220, 0xa0010}, {0x10c40, 0xa0010}, {0x641, 0xa0010}, {0x20640, 0xa0010}, {0x20341, 0xa0010}, {0x403c1, 0xa0010}, {0x30740, 0xa0010}, {0x316c0, 0xa0010}, {0x10043, 0x600110}, {0x70140, 0xa0010}, {0x70a40, 0xa0010}, {0x715c0, 0xa0010}, {0x18500c3, 0x180542}, {0x18500c6, 0x180542}, {0x60023, 0xd0670}, {0x60026, 0xd0670}, {0x68023, 0xd0770}, {0x68026, 0xd0770}, {0x70023, 0xd0870}, {0x70024, 0xd0870}, {0x5, 0x0}},
    {{0x80a0, 0xa0010}, {0x92a0, 0xa0010}, {0x10cc0, 0xa0010}, {0x6c1, 0xa0010}, {0x206c0, 0xa0010}, {0x203c1, 0xa0010}, {0x40441, 0xa0010}, {0x307c0, 0xa0010}, {0x31740, 0xa0010}, {0x100c3, 0x600110}, {0x701c0, 0xa0010}, {0x70ac0, 0xa0010}, {0x71640, 0xa0010}, {0x1850143, 0x180542}, {0x1850146, 0x180542}, {0x600a3, 0xd0670}, {0x600a6, 0xd0670}, {0x680a3, 0xd0770}, {0x680a6, 0xd0770}, {0x700a3, 0xd0870}, {0x700a4, 0xd0870}, {0x5, 0x0}},
    {{0x8120, 0xa0010}, {0x9320, 0xa0010}, {0x10d40, 0xa0010}, {0x741, 0xa0010}, {0x20740, 0xa0010}, {0x20441, 0xa0010}, {0x404c1, 0xa0010}, {0x30840, 0xa0010}, {0x317c0, 0xa0010}, {0x10143, 0x600110}, {0x70240, 0xa0010}, {0x70b40, 0xa0010}, {0x716c0, 0xa0010}, {0x18501c3, 0x180542}, {0x18501c6, 0x180542}, {0x60123, 0xd0670}, {0x60126, 0xd0670}, {0x68123, 0xd0770}, {0x68126, 0xd0770}, {0x70123, 0xd0870}, {0x70124, 0xd0870}, {0x5, 0x0}},
    {{0x81a0, 0xa0010}, {0x93a0, 0xa0010}, {0x10dc0, 0xa0010}, {0x10041, 0xa0010}, {0x207c0, 0xa0010}, {0x204c1, 0xa0010}, {0x40541, 0xa0010}, {0x308c0, 0xa0010}, {0x504c1, 0xa0010}, {0x40040, 0xa0010}, {0x408c0, 0xa0010}, {0x415c0, 0xa0010}, {0x20043, 0x600210}, {0x2450043, 0x180543}, {0x2450046, 0x180543}, {0x601a3, 0xd0670}, {0x601a6, 0xd0670}, {0x681a3, 0xd0770}, {0x681a6, 0xd0770}, {0x701a3, 0xd0870}, {0x701a4, 0xd0870}, {0x5, 0x0}},
    {{0x8220, 0xa0010}, {0x9420, 0xa0010}, {0x10e40, 0xa0010}, {0x100c1, 0xa0010}, {0x20840, 0xa0010}, {0x20541, 0xa0010}, {0x405c1, 0xa0010}, {0x30940, 0xa0010}, {0x50541, 0xa0010}, {0x400c0, 0xa0010}, {0x40940, 0xa0010}, {0x41640, 0xa0010}, {0x50140, 0xa0010}, {0x50ac0, 0xa0010}, {0x51540, 0xa0010}, {0x30043, 0x300320}, {0x30046, 0x300320}, {0x71240, 0xa0010}, {0x50043, 0x180540}, {0x50046, 0x180540}, {0x60223, 0xd0670}, {0x60226, 0xd0670}, {0x68223, 0xd0770}, {0x68226, 0xd0770}, {0x70223, 0xd0870}, {0x70224, 0xd0870}, {0x5, 0x0}},
    {{0x82a0, 0xa0010}, {0x94a0, 0xa0010}, {0x10ec0, 0xa0010}, {0x10141, 0xa0010}, {0x208c0, 0xa0010}, {0x205c1, 0xa0010}, {0x40641, 0xa0010}, {0x309c0, 0xa0010}, {0x505c1, 0xa0010}, {0x101c3, 0x600110}, {0x702c0, 0xa0010}, {0x401c3, 0x200430}, {0x401c6, 0x200430}, {0x6e0023, 0xe0671}, {0x6e0026, 0xe0671}, {0x6e8023, 0xe0771}, {0x6e8026, 0xe0771}, {0x6f0023, 0xe0871}, {0x6f0024, 0xe0871}, {0x5, 0x0}},
    {{0x8320, 0xa0010}, {0x9520, 0xa0010}, {0x10f40, 0xa0010}, {0x101c1, 0xa0010}, {0x20940, 0xa0010}, {0x20641, 0xa0010}, {0x406c1, 0xa0010}, {0x30a40, 0xa0010}, {0x50641, 0xa0010}, {0x40140, 0xa0010}, {0x409c0, 0xa0010}, {0x416c0, 0xa0010}, {0x501c0, 0xa0010}, {0x50b40, 0xa0010}, {0x515c0, 0xa0010}, {0x300c3, 0x300320}, {0x300c6, 0x300320}, {0x1040043, 0x200431}, {0x1040046, 0x200431}, {0x6e00a3, 0xe0671}, {0x6e00a6, 0xe0671}, {0x6e80a3, 0xe0771}, {0x6e80a6, 0xe0771}, {0x6f00a3, 0xe0871}, {0x6f00a4, 0xe0871}, {0x5, 0x0}},
    {{0x83a0, 0xa0010}, {0x95a0, 0xa0010}, {0x10fc0, 0xa0010}, {0x10241, 0xa0010}, {0x209c0, 0xa0010}, {0x206c1, 0xa0010}, {0x40741, 0xa0010}, {0x30ac0, 0xa0010}, {0x506c1, 0xa0010}, {0x10243, 0x600110}, {0x70340, 0xa0010}, {0x70bc0, 0xa0010}, {0x71740, 0xa0010}, {0x1850243, 0x180542}, {0x1850246, 0x180542}, {0x6e0123, 0xe0671}, {0x6e0126, 0xe0671}, {0x6e8123, 0xe0771}, {0x6e8126, 0xe0771}, {0x6f0123, 0xe0871}, {0x6f0124, 0xe0871}, {0x5, 0x0}},
    {{0x8420, 0xa0010}, {0x9620, 0xa0010}, {0x11040, 0xa0010}, {0x102c1, 0xa0010}, {0x20a40, 0xa0010}, {0x20741, 0xa0010}, {0x50041, 0xa0010}, {0x30b40, 0xa0010}, {0x50741, 0xa0010}, {0x401c0, 0xa0010}, {0x40a40, 0xa0010}, {0x41740, 0xa0010}, {0x200c3, 0x600210}, {0x24500c3, 0x180543}, {0x24500c6, 0x180543}, {0x6e01a3, 0xe0671}, {0x6e01a6, 0xe0671}, {0x6e81a3, 0xe0771}, {0x6e81a6, 0xe0771}, {0x6f01a3, 0xe0871}, {0x6f01a4, 0xe0871}, {0x5, 0x0}},
    {{0x84a0, 0xa0010}, {0x96a0, 0xa0010}, {0x110c0, 0xa0010}, {0x10341, 0xa0010}, {0x20ac0, 0xa0010}, {0x30041, 0xa0010}, {0x500c1, 0xa0010}, {0x30bc0, 0xa0010}, {0x60041, 0xa0010}, {0x40240, 0xa0010}, {0x40ac0, 0xa0010}, {0x417c0, 0xa0010}, {0x50240, 0xa0010}, {0x50bc0, 0xa0010}, {0x51640, 0xa0010}, {0x30143, 0x300320}, {0x30146, 0x300320}, {0x712c0, 0xa0010}, {0x500c3, 0x180540}, {0x500c6, 0x180540}, {0x6e0223, 0xe0671}, {0x6e0226, 0xe0671}, {0x6e8223, 0xe0771}, {0x6e8226, 0xe0771}, {0x6f0223, 0xe0871}, {0x6f0224, 0xe0871}, {0x5, 0x0}},
    {{0x8520, 0xa0010}, {0x9720, 0xa0010}, {0x11140, 0xa0010}, {0x103c1, 0xa0010}, {0x20b40, 0xa0010}, {0x300c1, 0xa0010}, {0x50141, 0xa0010}, {0x30c40, 0xa0010}, {0x600c1, 0xa0010}, {0x703c1, 0xa0010}, {0x40b40, 0xa0010}, {0xc2, 0xa0010}, {0x502c0, 0xa0010}, {0x50c40, 0xa0010}, {0x516c0, 0xa0010}, {0x301c3, 0x300320}, {0x301c6, 0x300320}, {0x10400c3, 0x200431}, {0x10400c6, 0x200431}, {0xde0023, 0xe0672}, {0xde0026, 0xe0672}, {0xde8023, 0xe0772}, {0xde8026, 0xe0772}, {0xdf0023, 0xe0872}, {0xdf0024, 0xe0872}, {0x5, 0x0}},
    {{0x85a0, 0xa0010}, {0x97a0, 0xa0010}, {0x111c0, 0xa0010}, {0x10441, 0xa0010}, {0x20bc0, 0xa0010}, {0x30141, 0xa0010}, {0x501c1, 0xa0010}, {0x30cc0, 0xa0010}, {0x60141, 0xa0010}, {0x70441, 0xa0010}, {0x40bc0, 0xa0010}, {0x142, 0xa0010}, {0x20143, 0x600210}, {0x2450143, 0x180543}, {0x2450146, 0x180543}, {0xde00a3, 0xe0672}, {0xde00a6, 0xe0672}, {0xde80a3, 0xe0772}, {0xde80a6, 0xe0772}, {0xdf00a3, 0xe0872}, {0xdf00a4, 0xe0872}, {0x5, 0x0}},
    {{0x8620, 0xa0010}, {0x10040, 0xa0010}, {0x11240, 0xa0010}, {0x20040, 0xa0010}, {0x20c40, 0xa0010}, {0x43, 0x600010}, {0x603c0, 0xa0010}, {0x60c40, 0xa0010}, {0x61440, 0xa0010}, {0x701c2, 0xa0010}, {0x70940, 0xa0010}, {0x71140, 0xa0010}, {0x50143, 0x180540}, {0x50146, 0x180540}, {0xde0123, 0xe0672}, {0xde0126, 0xe0672}, {0xde8123, 0xe0772}, {0xde8126, 0xe0772}, {0xdf0123, 0xe0872}, {0xdf0124, 0xe0872}, {0x5, 0x0}},
    {{0x86a0, 0xa0010}, {0x100c0, 0xa0010}, {0x112c0, 0xa0010}, {0x200c0, 0xa0010}, {0x20cc0, 0xa0010}, {0xc3, 0x600010}, {0x60440, 0xa0010}, {0x1830243, 0x300321}, {0x1830246, 0x300321}, {0x717c0, 0xa0010}, {0x24501c3, 0x180543}, {0x24501c6, 0x180543}, {0xde01a3, 0xe0672}, {0xde01a6, 0xe0672}, {0xde81a3, 0xe0772}, {0xde81a6, 0xe0772}, {0xdf01a3, 0xe0872}, {0xdf01a4, 0xe0872}, {0x5, 0x0}},
    {{0x8720, 0xa0010}, {0x10140, 0xa0010}, {0x11340, 0xa0010}, {0x20140, 0xa0010}, {0x20d40, 0xa0010}, {0x143, 0x600010}, {0x604c0, 0xa0010}, {0x60cc0, 0xa0010}, {0x614c0, 0xa0010}, {0x70242, 0xa0010}, {0x400c3, 0x200430}, {0x400c6, 0x200430}, {0xde0223, 0xe0672}, {0xde0226, 0xe0672}, {0xde8223, 0xe0772}, {0xde8226, 0xe0772}, {0xdf0223, 0xe0872}, {0xdf0224, 0xe0872}, {0x5, 0x0}},
    {{0x87a0, 0xa0010}, {0x101c0, 0xa0010}, {0x113c0, 0xa0010}, {0x201c0, 0xa0010}, {0x20dc0, 0xa0010}, {0x1c3, 0x600010}, {0x60540, 0xa0010}, {0x60d40, 0xa0010}, {0x60042, 0xa0010}, {0x70040, 0xa0010}, {0x709c0, 0xa0010}, {0x711c0, 0xa0010}, {0x501c3, 0x180540}, {0x501c6, 0x180540}, {0x14e0023, 0xd0673}, {0x14e0026, 0xd0673}, {0x14e8023, 0xd0773}, {0x14e8026, 0xd0773}, {0x14f0023, 0xd0873}, {0x14f0024, 0xd0873}, {0x5, 0x0}},
    {{0x8820, 0xa0010}, {0x10240, 0xa0010}, {0x11440, 0xa0010}, {0x20240, 0xa0010}, {0x20e40, 0xa0010}, {0x243, 0x600010}, {0x605c0, 0xa0010}, {0x60dc0, 0xa0010}, {0x600c2, 0xa0010}, {0x700c0, 0xa0010}, {0x40143, 0x200430}, {0x40146, 0x200430}, {0x14e00a3, 0xd0673}, {0x14e00a6, 0xd0673}, {0x14e80a3, 0xd0773}, {0x14e80a6, 0xd0773}, {0x14f00a3, 0xd0873}, {0x14f00a4, 0xd0873}, {0x5, 0x0}},
    {{0x88a0, 0xa0010}, {0x102c0, 0xa0010}, {0x114c0, 0xa0010}, {0x202c0, 0xa0010}, {0x20ec0, 0xa0010}, {0x301c1, 0xa0010}, {0x30040, 0xa0010}, {0x30d40, 0xa0010}, {0x601c1, 0xa0010}, {0x402c0, 0xa0010}, {0x40c40, 0xa0010}, {0x1c2, 0xa0010}, {0x50340, 0xa0010}, {0x50cc0, 0xa0010}, {0x51740, 0xa0010}, {0x60640, 0xa0010}, {0x60e40, 0xa0010}, {0x61540, 0xa0010}, {0x703c0, 0xa0010}, {0x70c40, 0xa0010}, {0x1040143, 0x200431}, {0x1040146, 0x200431}, {0x14e0123, 0xd0673}, {0x14e0126, 0xd0673}, {0x14e8123, 0xd0773}, {0x14e8126, 0xd0773}, {0x14f0123, 0xd0873}, {0x14f0124, 0xd0873}, {0x5, 0x0}},
    {{0x8920, 0xa0010}, {0x10340, 0xa0010}, {0x11540, 0xa0010}, {0x20340, 0xa0010}, {0x20f40, 0xa0010}, {0x30241, 0xa0010}, {0x300c0, 0xa0010}, {0x30dc0, 0xa0010}, {0x60241, 0xa0010}, {0x40340, 0xa0010}, {0x40cc0, 0xa0010}, {0x242, 0xa0010}, {0x503c0, 0xa0010}, {0x50d40, 0xa0010}, {0x517c0, 0xa0010}, {0x606c0, 0xa0010}, {0x60ec0, 0xa0010}, {0x615c0, 0xa0010}, {0x70440, 0xa0010}, {0x70cc0, 0xa0010}, {0x10401c3, 0x200431}, {0x10401c6, 0x200431}, {0x14e01a3, 0xd0673}, {0x14e01a6, 0xd0673}, {0x14e81a3, 0xd0773}, {0x14e81a6, 0xd0773}, {0x14f01a3, 0xd0873}, {0x14f01a4, 0xd0873}, {0x5, 0x0}},
    {{0x89a0, 0xa0010}, {0x103c0, 0xa0010}, {0x115c0, 0xa0010}, {0x203c0, 0xa0010}, {0x20fc0, 0xa0010}, {0x302c1, 0xa0010}, {0x30140, 0xa0010}, {0x30e40, 0xa0010}, {0x602c1, 0xa0010}, {0x403c0, 0xa0010}, {0x40d40, 0xa0010}, {0x10042, 0xa0010}, {0x50440, 0xa0010}, {0x50dc0, 0xa0010}, {0x40142, 0xa0010}, {0x60740, 0xa0010}, {0x60f40, 0xa0010}, {0x61640, 0xa0010}, {0x704c0, 0xa0010}, {0x70d40, 0xa0010}, {0x1040243, 0x200431}, {0x1040246, 0x200431}, {0x14e0223, 0xd0673}, {0x14e0226, 0xd0673}, {0x14e8223, 0xd0773}, {0x14e8226, 0xd0773}, {0x14f0223, 0xd0873}, {0x14f0224, 0xd0873}, {0x5, 0x0}},
    {{0x8a20, 0xa0010}, {0x10440, 0xa0010}, {0x11640, 0xa0010}, {0x20440, 0xa0010}, {0x21040, 0xa0010}, {0x30341, 0xa0010}, {0x301c0, 0xa0010}, {0x30ec0, 0xa0010}, {0x60341, 0xa0010}, {0x40440, 0xa0010}, {0x40dc0, 0xa0010}, {0x100c2, 0xa0010}, {0x504c0, 0xa0010}, {0x50e40, 0xa0010}, {0x401c2, 0xa0010}, {0x607c0, 0xa0010}, {0x60fc0, 0xa0010}, {0x616c0, 0xa0010}, {0x70540, 0xa0010}, {0x70dc0, 0xa0010}, {0x2040043, 0x200432}, {0x2040046, 0x200432}, {0x1b60023, 0xe0674}, {0x1b60026, 0xe0674}, {0x1b68023, 0xe0774}, {0x1b68026, 0xe0774}, {0x1b70023, 0xe0874}, {0x1b70024, 0xe0874}, {0x5, 0x0}},
    {{0x8aa0, 0xa0010}, {0x104c0, 0xa0010}, {0x116c0, 0xa0010}, {0x204c0, 0xa0010}, {0x210c0, 0xa0010}, {0x303c1, 0xa0010}, {0x30240, 0xa0010}, {0x30f40, 0xa0010}, {0x603c1, 0xa0010}, {0x404c0, 0xa0010}, {0x40e40, 0xa0010}, {0x10142, 0xa0010}, {0x50540, 0xa0010}, {0x50ec0, 0xa0010}, {0x40242, 0xa0010}, {0x60840, 0xa0010}, {0x61040, 0xa0010}, {0x61740, 0xa0010}, {0x705c0, 0xa0010}, {0x70e40, 0xa0010}, {0x20400c3, 0x200432}, {0x20400c6, 0x200432}, {0x1b600a3, 0xe0674}, {0x1b600a6, 0xe0674}, {0x1b680a3, 0xe0774}, {0x1b680a6, 0xe0774}, {0x1b700a3, 0xe0874}, {0x1b700a4, 0xe0874}, {0x5, 0x0}},
    {{0x8b20, 0xa0010}, {0x10540, 0xa0010}, {0x11740, 0xa0010}, {0x20540, 0xa0010}, {0x21140, 0xa0010}, {0x30441, 0xa0010}, {0x302c0, 0xa0010}, {0x30fc0, 0xa0010}, {0x60441, 0xa0010}, {0x40540, 0xa0010}, {0x40ec0, 0xa0010}, {0x101c2, 0xa0010}, {0x505c0, 0xa0010}, {0x50f40, 0xa0010}, {0x50042, 0xa0010}, {0x30243, 0x300320}, {0x30246, 0x300320}, {0x71340, 0xa0010}, {0xc500c3, 0x180541}, {0xc500c6, 0x180541}, {0x1b60123, 0xe0674}, {0x1b60126, 0xe0674}, {0x1b68123, 0xe0774}, {0x1b68126, 0xe0774}, {0x1b70123, 0xe0874}, {0x1b70124, 0xe0874}, {0x5, 0x0}},
    {{0x8ba0, 0xa0010}, {0x105c0, 0xa0010}, {0x117c0, 0xa0010}, {0x205c0, 0xa0010}, {0x211c0, 0xa0010}, {0x304c1, 0xa0010}, {0x30340, 0xa0010}, {0x31040, 0xa0010}, {0x604c1, 0xa0010}, {0x405c0, 0xa0010}, {0x40f40, 0xa0010}, {0x10242, 0xa0010}, {0x50640, 0xa0010}, {0x50fc0, 0xa0010}, {0x500c2, 0xa0010}, {0x608c0, 0xa0010}, {0x610c0, 0xa0010}, {0x617c0, 0xa0010}, {0x70640, 0xa0010}, {0x70ec0, 0xa0010}, {0x2040143, 0x200432}, {0x2040146, 0x200432}, {0x1b601a3, 0xe0674}, {0x1b601a6, 0xe0674}, {0x1b681a3, 0xe0774}, {0x1b681a6, 0xe0774}, {0x1b701a3, 0xe0874}, {0x1b701a4, 0xe0874}, {0x5, 0x0}},
    {{0x8c20, 0xa0010}, {0x10640, 0xa0010}, {0x41, 0xa0010}, {0x104c1, 0xa0010}, {0x21240, 0xa0010}, {0x30541, 0xa0010}, {0x303c0, 0xa0010}, {0x310c0, 0xa0010}, {0x60541, 0xa0010}, {0x40640, 0xa0010}, {0x40fc0, 0xa0010}, {0x20042, 0xa0010}, {0x506c0, 0xa0010}, {0x51040, 0xa0010}, {0x50142, 0xa0010}, {0x1830043, 0x300321}, {0x1830046, 0x300321}, {0x713c0, 0xa0010}, {0xc50143, 0x180541}, {0xc50146, 0x180541}, {0x1b60223, 0xe0674}, {0x1b60226, 0xe0674}, {0x1b68223, 0xe0774}, {0x1b68226, 0xe0774}, {0x1b70223, 0xe0874}, {0x1b70224, 0xe0874}, {0x5, 0x0}},
    {{0x8ca0, 0xa0010}, {0x106c0, 0xa0010}, {0xc1, 0xa0010}, {0x10541, 0xa0010}, {0x212c0, 0xa0010}, {0x305c1, 0xa0010}, {0x30440, 0xa0010}, {0x31140, 0xa0010}, {0x605c1, 0xa0010}, {0x406c0, 0xa0010}, {0x41040, 0xa0010}, {0x200c2, 0xa0010}, {0x50740, 0xa0010}, {0x510c0, 0xa0010}, {0x501c2, 0xa0010}, {0x60940, 0xa0010}, {0x61140, 0xa0010}, {0x60142, 0xa0010}, {0x706c0, 0xa0010}, {0x70f40, 0xa0010}, {0x20401c3, 0x200432}, {0x20401c6, 0x200432}, {0x2260023, 0xe0675}, {0x2260026, 0xe0675}, {0x2268023, 0xe0775}, {0x2268026, 0xe0775}, {0x2270023, 0xe0875}, {0x2270024, 0xe0875}, {0x5, 0x0}},
    {{0x8d20, 0xa0010}, {0x10740, 0xa0010}, {0x141, 0xa0010}, {0x105c1, 0xa0010}, {0x21340, 0xa0010}, {0x30641, 0xa0010}, {0x304c0, 0xa0010}, {0x311c0, 0xa0010}, {0x60641, 0xa0010}, {0x40740, 0xa0010}, {0x410c0, 0xa0010}, {0x20142, 0xa0010}, {0x507c0, 0xa0010}, {0x51140, 0xa0010}, {0x50242, 0xa0010}, {0x609c0, 0xa0010}, {0x611c0, 0xa0010}, {0x601c2, 0xa0010}, {0x70740, 0xa0010}, {0x70fc0, 0xa0010}, {0x2040243, 0x200432}, {0x2040246, 0x200432}, {0x22600a3, 0xe0675}, {0x22600a6, 0xe0675}, {0x22680a3, 0xe0775}, {0x22680a6, 0xe0775}, {0x22700a3, 0xe0875}, {0x22700a4, 0xe0875}, {0x5, 0x0}},
    {{0x8da0, 0xa0010}, {0x107c0, 0xa0010}, {0x1c1, 0xa0010}, {0x10641, 0xa0010}, {0x213c0, 0xa0010}, {0x306c1, 0xa0010}, {0x30540, 0xa0010}, {0x31240, 0xa0010}, {0x606c1, 0xa0010}, {0x407c0, 0xa0010}, {0x41140, 0xa0010}, {0x201c2, 0xa0010}, {0x50840, 0xa0010}, {0x511c0, 0xa0010}, {0x60040, 0xa0010}, {0x18300c3, 0x300321}, {0x18300c6, 0x300321}, {0x71440, 0xa0010}, {0xc501c3, 0x180541}, {0xc501c6, 0x180541}, {0x2260123, 0xe0675}, {0x2260126, 0xe0675}, {0x2268123, 0xe0775}, {0x2268126, 0xe0775}, {0x2270123, 0xe0875}, {0x2270124, 0xe0875}, {0x5, 0x0}},
    {{0x8e20, 0xa0010}, {0x10840, 0xa0010}, {0x241, 0xa0010}, {0x106c1, 0xa0010}, {0x21440, 0xa0010}, {0x30741, 0xa0010}, {0x305c0, 0xa0010}, {0x312c0, 0xa0010}, {0x60741, 0xa0010}, {0x40840, 0xa0010}, {0x411c0, 0xa0010}, {0x20242, 0xa0010}, {0x508c0, 0xa0010}, {0x51240, 0xa0010}, {0x600c0, 0xa0010}, {0x60a40, 0xa0010}, {0x61240, 0xa0010}, {0x60242, 0xa0010}, {0x707c0, 0xa0010}, {0x71040, 0xa0010}, {0x50243, 0x180540}, {0x50246, 0x180540}, {0x22601a3, 0xe0675}, {0x22601a6, 0xe0675}, {0x22681a3, 0xe0775}, {0x22681a6, 0xe0775}, {0x22701a3, 0xe0875}, {0x22701a4, 0xe0875}, {0x5, 0x0}},
    {{0x8ea0, 0xa0010}, {0x108c0, 0xa0010}, {0x2c1, 0xa0010}, {0x10741, 0xa0010}, {0x214c0, 0xa0010}, {0x40041, 0xa0010}, {0x30640, 0xa0010}, {0x31340, 0xa0010}, {0x70041, 0xa0010}, {0x704c1, 0xa0010}, {0x41240, 0xa0010}, {0x30042, 0xa0010}, {0x201c3, 0x600210}, {0x2450243, 0x180543}, {0x2450246, 0x180543}, {0x5, 0x0}},
    {{0x8f20, 0xa0010}, {0x10940, 0xa0010}, {0x341, 0xa0010}, {0x20041, 0xa0010}, {0x21540, 0xa0010}, {0x400c1, 0xa0010}, {0x306c0, 0xa0010}, {0x313c0, 0xa0010}, {0x700c1, 0xa0010}, {0x70541, 0xa0010}, {0x412c0, 0xa0010}, {0x300c2, 0xa0010}, {0x50940, 0xa0010}, {0x512c0, 0xa0010}, {0x60140, 0xa0010}, {0x1830143, 0x300321}, {0x1830146, 0x300321}, {0x714c0, 0xa0010}, {0xc50243, 0x180541}, {0xc50246, 0x180541}, {0x2260223, 0xe0675}, {0x2260226, 0xe0675}, {0x2268223, 0xe0775}, {0x2268226, 0xe0775}, {0x2270223, 0xe0875}, {0x2270224, 0xe0875}, {0x5, 0x0}},
    {{0x8fa0, 0xa0010}, {0x109c0, 0xa0010}, {0x3c1, 0xa0010}, {0x200c1, 0xa0010}, {0x215c0, 0xa0010}, {0x40141, 0xa0010}, {0x50241, 0xa0010}, {0x31440, 0xa0010}, {0x70141, 0xa0010}, {0x705c1, 0xa0010}, {0x41340, 0xa0010}, {0x30142, 0xa0010}, {0x20243, 0x600210}, {0x2960023, 0xe0676}, {0x2960026, 0xe0676}, {0x2968023, 0xe0776}, {0x2968026, 0xe0776}, {0x2970023, 0xe0876}, {0x2970024, 0xe0876}, {0x5, 0x0}},
    {{0x9020, 0xa0010}, {0x10a40, 0xa0010}, {0x441, 0xa0010}, {0x20141, 0xa0010}, {0x21640, 0xa0010}, {0x401c1, 0xa0010}, {0x502c1, 0xa0010}, {0x314c0, 0xa0010}, {0x701c1, 0xa0010}, {0x70641, 0xa0010}, {0x413c0, 0xa0010}, {0x301c2, 0xa0010}, {0x509c0, 0xa0010}, {0x51340, 0xa0010}, {0x601c0, 0xa0010}, {0x60ac0, 0xa0010}, {0x612c0, 0xa0010}, {0x70042, 0xa0010}, {0x40043, 0x200430}, {0x40046, 0x200430}, {0x29600a3, 0xe0676}, {0x29600a6, 0xe0676}, {0x29680a3, 0xe0776}, {0x29680a6, 0xe0776}, {0x29700a3, 0xe0876}, {0x29700a4, 0xe0876}, {0x5, 0x0}},
    {{0x90a0, 0xa0010}, {0x10ac0, 0xa0010}, {0x4c1, 0xa0010}, {0x201c1, 0xa0010}, {0x216c0, 0xa0010}, {0x40241, 0xa0010}, {0x50341, 0xa0010}, {0x31540, 0xa0010}, {0x70241, 0xa0010}, {0x706c1, 0xa0010}, {0x41440, 0xa0010}, {0x30242, 0xa0010}, {0x50a40, 0xa0010}, {0x513c0, 0xa0010}, {0x60240, 0xa0010}, {0x60b40, 0xa0010}, {0x61340, 0xa0010}, {0x700c2, 0xa0010}, {0x70840, 0xa0010}, {0x710c0, 0xa0010}, {0xc50043, 0x180541}, {0xc50046, 0x180541}, {0x2960123, 0xe0676}, {0x2960126, 0xe0676}, {0x2968123, 0xe0776}, {0x2968126, 0xe0776}, {0x2970123, 0xe0876}, {0x2970124, 0xe0876}, {0x5, 0x0}},
    {{0x9120, 0xa0010}, {0x10b40, 0xa0010}, {0x541, 0xa0010}, {0x20241, 0xa0010}, {0x21740, 0xa0010}, {0x402c1, 0xa0010}, {0x503c1, 0xa0010}, {0x315c0, 0xa0010}, {0x702c1, 0xa0010}, {0x70741, 0xa0010}, {0x414c0, 0xa0010}, {0x50040, 0xa0010}, {0x40042, 0xa0010}, {0x51440, 0xa0010}, {0x602c0, 0xa0010}, {0x18301c3, 0x300321}, {0x18301c6, 0x300321}, {0x71540, 0xa0010}, {0x1850043, 0x180542}, {0x1850046, 0x180542}, {0x29601a3, 0xe0676}, {0x29601a6, 0xe0676}, {0x29681a3, 0xe0776}, {0x29681a6, 0xe0776}, {0x29701a3, 0xe0876}, {0x29701a4, 0xe0876}, {0x5, 0x0}},
    {{0x91a0, 0xa0010}, {0x10bc0, 0xa0010}, {0x5c1, 0xa0010}, {0x202c1, 0xa0010}, {0x217c0, 0xa0010}, {0x40341, 0xa0010}, {0x50441, 0xa0010}, {0x31640, 0xa0010}, {0x70341, 0xa0010}, {0x42, 0xa0010}, {0x41540, 0xa0010}, {0x500c0, 0xa0010}, {0x400c2, 0xa0010}, {0x514c0, 0xa0010}, {0x60340, 0xa0010}, {0x60bc0, 0xa0010}, {0x613c0, 0xa0010}, {0x70142, 0xa0010}, {0x708c0, 0xa0010}, {0x40243, 0x200430}, {0x40246, 0x200430}, {0x2960223, 0xe0676}, {0x2960226, 0xe0676}, {0x2968223, 0xe0776}, {0x2968226, 0xe0776}, {0x2970223, 0xe0876}, {0x2970224, 0xe0876}, {0x5, 0x0}}
}};
#define D8(i) "+f"(d[i]), "+f"(d[i + 1]), "+f"(d[i + 2]), "+f"(d[i + 3]), "+f"(d[i + 4]), "+f"(d[i + 5]), "+f"(d[i + 6]), "+f"(d[i + 7])
template <int N> __device__ __forceinline__ void wgmma_side(float* d, uint32_t alo, uint32_t blo, int sc);
template <> __device__ __forceinline__ void wgmma_side<128>(float* d, uint32_t alo, uint32_t blo, int sc) {
    asm volatile("{.reg .pred p; .reg .b64 ad, bd; setp.ne.b32 p, %66, 0; mov.b64 ad, {%64, 0x40000040}; mov.b64 bd, {%65, 0x40000040};\n"
                 "wgmma.mma_async.sync.aligned.m64n128k16.f32.bf16.bf16 "
                 "{%0,%1,%2,%3,%4,%5,%6,%7,%8,%9,%10,%11,%12,%13,%14,%15,%16,%17,%18,%19,%20,%21,%22,%23,%24,%25,%26,%27,%28,%29,%30,%31,"
                 "%32,%33,%34,%35,%36,%37,%38,%39,%40,%41,%42,%43,%44,%45,%46,%47,%48,%49,%50,%51,%52,%53,%54,%55,%56,%57,%58,%59,%60,%61,%62,%63},"
                 " ad, bd, p, 1, 1, 1, 0;}"
                 : D8(0), D8(8), D8(16), D8(24), D8(32), D8(40), D8(48), D8(56)
                 : "r"(alo), "r"(blo), "r"(sc));
}
template <> __device__ __forceinline__ void wgmma_side<192>(float* d, uint32_t alo, uint32_t blo, int sc) {
    asm volatile("{.reg .pred p; .reg .b64 ad, bd; setp.ne.b32 p, %98, 0; mov.b64 ad, {%96, 0x40000040}; mov.b64 bd, {%97, 0x40000040};\n"
                 "wgmma.mma_async.sync.aligned.m64n192k16.f32.bf16.bf16 "
                 "{%0,%1,%2,%3,%4,%5,%6,%7,%8,%9,%10,%11,%12,%13,%14,%15,%16,%17,%18,%19,%20,%21,%22,%23,%24,%25,%26,%27,%28,%29,%30,%31,"
                 "%32,%33,%34,%35,%36,%37,%38,%39,%40,%41,%42,%43,%44,%45,%46,%47,%48,%49,%50,%51,%52,%53,%54,%55,%56,%57,%58,%59,%60,%61,%62,%63,"
                 "%64,%65,%66,%67,%68,%69,%70,%71,%72,%73,%74,%75,%76,%77,%78,%79,%80,%81,%82,%83,%84,%85,%86,%87,%88,%89,%90,%91,%92,%93,%94,%95},"
                 " ad, bd, p, 1, 1, 1, 0;}"
                 : D8(0), D8(8), D8(16), D8(24), D8(32), D8(40), D8(48), D8(56), D8(64), D8(72), D8(80), D8(88)
                 : "r"(alo), "r"(blo), "r"(sc));
}
template <> __device__ __forceinline__ void wgmma_side<256>(float* d, uint32_t alo, uint32_t blo, int sc) {
    asm volatile("{.reg .pred p; .reg .b64 ad, bd; setp.ne.b32 p, %130, 0; mov.b64 ad, {%128, 0x40000040}; mov.b64 bd, {%129, 0x40000040};\n"
                 "wgmma.mma_async.sync.aligned.m64n256k16.f32.bf16.bf16 "
                 "{%0,%1,%2,%3,%4,%5,%6,%7,%8,%9,%10,%11,%12,%13,%14,%15,%16,%17,%18,%19,%20,%21,%22,%23,%24,%25,%26,%27,%28,%29,%30,%31,"
                 "%32,%33,%34,%35,%36,%37,%38,%39,%40,%41,%42,%43,%44,%45,%46,%47,%48,%49,%50,%51,%52,%53,%54,%55,%56,%57,%58,%59,%60,%61,%62,%63,"
                 "%64,%65,%66,%67,%68,%69,%70,%71,%72,%73,%74,%75,%76,%77,%78,%79,%80,%81,%82,%83,%84,%85,%86,%87,%88,%89,%90,%91,%92,%93,%94,%95,"
                 "%96,%97,%98,%99,%100,%101,%102,%103,%104,%105,%106,%107,%108,%109,%110,%111,%112,%113,%114,%115,%116,%117,%118,%119,%120,%121,%122,%123,%124,%125,%126,%127},"
                 " ad, bd, p, 1, 1, 1, 0;}"
                 : D8(0), D8(8), D8(16), D8(24), D8(32), D8(40), D8(48), D8(56), D8(64), D8(72), D8(80), D8(88), D8(96), D8(104), D8(112), D8(120)
                 : "r"(alo), "r"(blo), "r"(sc));
}
#undef D8

__device__ __forceinline__ void bulk_st(void* dst, uint32_t src, uint32_t bytes) {
    asm volatile("cp.async.bulk.global.shared::cta.bulk_group [%0], [%1], %2;" :: "l"(dst), "r"(src), "r"(bytes) : "memory");
}
__device__ __forceinline__ void red_release(uint32_t* p, uint32_t v) { asm volatile("red.release.gpu.global.add.u32 [%0], %1;" :: "l"(p), "r"(v) : "memory"); }
__device__ __forceinline__ void wait_ge(const uint32_t* p, uint32_t v) { for (int c = 0; c < SPIN_LIM && (int)(ld_acquire(p) - v) < 0; c++) { } }
__device__ __forceinline__ uint4* part_ptr(Job job, int wg) {
    return g_op + (size_t)((job.x >> 13) & 63) * (10 * NKS * 256) + (((job.x >> 7) & 63) * 2 + wg) * NKS * ((job.x >> 3) & 15) * 256;
}

template <int T>
__device__ __forceinline__ void side_job(Job job, uint32_t& it, uint32_t& n, uint32_t sb, uint32_t sa, int wg, int t)
{
    float acc[T / 2];
#pragma unroll
    for (int i = 0; i < T / 2; i++) acc[i] = 0.f;
    const int nkb = job.y >> 16;
    constexpr uint32_t NS = SST, SZ = S_STAGE, BO = 0;
    uint32_t prev = 0;
    for (int kb = 0; kb < nkb; kb++, it++) {
        const uint32_t st = it % NS;
        const uint32_t alo = ((sb + st * SZ + wg * 8192) >> 4) | (64u << 16), blo = ((sb + st * SZ + 16384) >> 4) | (1u << 16);
        mbar_wait_long(sb + SB_FULL + BO + 8 * st, (it / NS) & 1);
        wg_fence();
#pragma unroll
        for (int k4 = 0; k4 < 4; k4++) wgmma_side<T>(acc, alo + k4 * 128, blo + k4 * 2, kb | k4);
        wg_commit();
        if (kb) { wg_wait<1>(); arrive_e(prev); }
        prev = sb + SB_EMPTY + BO + 8 * st;
    }
    if (n) mbar_wait_long(sb + SB_FREE, (n - 1) & 1);
    n++;
    wg_wait<0>();
    arrive_e(prev);
    const bool raw = (job.x & 7) == JV || (job.y & 0xf0) != 0x10;
#pragma unroll
    for (int u = 0; u < T / 16; u++) {
        const uint4 w = make_uint4(pack2(acc[8 * u], acc[8 * u + 1]), pack2(acc[8 * u + 2], acc[8 * u + 3]),
                                   pack2(acc[8 * u + 4], acc[8 * u + 5]), pack2(acc[8 * u + 6], acc[8 * u + 7]));
        if (raw || T != 256) sts4(sb + S_STG + wg * 32768 + t * 16 + u * 2048, w);
        else stsm4t(sb + S_STG + wg * 32768 + sa + u * 2048, w.x, w.y, w.z, w.w);
    }
    asm volatile("fence.proxy.async.shared::cta;" ::: "memory");
    __syncwarp();
    arrive_e(sb + SB_STAGED + 8 * wg);
}

template <int NS>
__device__ __forceinline__ void side_sum(Job job, uint32_t& n, uint32_t sb, uint32_t sa, int wg, int t)
{
    constexpr int NU = (16 + NS - 1) / NS;
    const int ks = job.y & 15, nb = (job.x >> 3) & 15;
    const uint4* part = part_ptr(job, wg) + ks * 128 + t;
    uint4 q[NU][NS];
#pragma unroll
    for (int i = 0; i < NU; i++) {
#pragma unroll
        for (int k = 0; k < NS; k++) q[i][k] = make_uint4(0, 0, 0, 0);
        if (ks + i * NS < 2 * nb) {
#pragma unroll
            for (int k = 0; k < NS; k++) q[i][k] = ld_pkt(part + k * nb * 256 + i * NS * 128);
        }
    }
    if (n) mbar_wait_long(sb + SB_FREE, (n - 1) & 1);
    n++;
#pragma unroll
    for (int i = 0; i < NU; i++)
        if (ks + i * NS < 2 * nb) {
            float r[8] = {0, 0, 0, 0, 0, 0, 0, 0};
#pragma unroll
            for (int k = 0; k < NS; k++) {
                r[0] += bf_lo(q[i][k].x); r[1] += bf_hi(q[i][k].x); r[2] += bf_lo(q[i][k].y); r[3] += bf_hi(q[i][k].y);
                r[4] += bf_lo(q[i][k].z); r[5] += bf_hi(q[i][k].z); r[6] += bf_lo(q[i][k].w); r[7] += bf_hi(q[i][k].w);
            }
            stsm4t(sb + S_STG + wg * 32768 + sa + i * 2048, pack2(r[0], r[1]), pack2(r[2], r[3]), pack2(r[4], r[5]), pack2(r[6], r[7]));
        }
    asm volatile("fence.proxy.async.shared::cta;" ::: "memory");
    __syncwarp();
    arrive_e(sb + SB_STAGED + 8 * wg);
}

__device__ __forceinline__ void ld20(const bf16* p, uint32_t* w) {
#pragma unroll
    for (int i = 0; i < 5; i++) asm volatile("ld.global.v2.b32 {%0,%1}, [%2];" : "=r"(w[2 * i]), "=r"(w[2 * i + 1]) : "l"(p + 4 * i) : "memory");
}

__global__ void __launch_bounds__(384, 1) side_kernel(const __grid_constant__ SideParams P)
{
    extern __shared__ __align__(1024) uint8_t smem[];
    const uint32_t sb = smem_u32(smem);
    const int tid = threadIdx.x, lane = tid & 31;
    const int warp = __shfl_sync(0xffffffffu, tid >> 5, 0);
    if (tid == 0) {
        TLS(96 + blockIdx.x, 71);
        for (int i = 0; i < SST; i++) { mbar_init(sb + SB_FULL + 8 * i, 1); mbar_init(sb + SB_EMPTY + 8 * i, 8); }
        mbar_init(sb + SB_STAGED, 4); mbar_init(sb + SB_STAGED + 8, 4); mbar_init(sb + SB_FREE, 1);
        asm volatile("fence.mbarrier_init.release.cluster;" ::: "memory");
    }
    __syncthreads();
#ifdef NOSIDE
    if (EPC) return;
    { const uint32_t ep = ld_epoch(); asm volatile("griddepcontrol.wait;" ::: "memory"); if (blockIdx.x == 0 && tid == 0) g_epoch = ep; return; }
#endif
    const Job* jobs = c_jobs.j[blockIdx.x];
    if (warp < 8) {
        asm volatile("setmaxnreg.inc.sync.aligned.u32 192;");
        const uint32_t ep = ld_epoch();
        uint32_t it = 0, n = 0;
        const int wg = warp >> 2, t = tid & 127;
        const uint32_t sa = ((lane & 7) + ((lane >> 4) << 3)) * 128 + (((2 * (t >> 5) + ((lane >> 3) & 1)) ^ (lane & 7)) << 4);
        for (int j = 0; ; j++) {
            const Job job = jobs[j];
            if (tid == 0 && (jobs[j].x & 7) != JS) TLS(96 + blockIdx.x, j);
            const int type = job.x & 7, nb = (job.x >> 3) & 15;
            if (type == JEND) break;
            if (type == JS) continue;
            if (type == JR) {
                const int ns = (job.y >> 4) & 15;
                if (t == 0) wait_ge(g_cnt + CNT_O + ((job.y >> 8) & 255) * 5 + ((job.x >> 7) & 63), ep * ns);
                bar_sync(1 + wg, 128);
                side_sum<NKS>(job, n, sb, sa, wg, t);
                continue;
            }
            switch (nb) {
                case 8: side_job<256>(job, it, n, sb, sa, wg, t); break;
                case 6: side_job<192>(job, it, n, sb, sa, wg, t); break;
                default: side_job<128>(job, it, n, sb, sa, wg, t); break;
            }
        }

        if (tid == 0) TLS(96 + blockIdx.x, 70);
    } else {
        asm volatile("setmaxnreg.dec.sync.aligned.u32 120;");
        if (warp == 8) {
            const uint32_t ns = SST, sz = S_STAGE, bo = sb;
            uint32_t ep = 0, sa = 0, pa = 1, sl = 0;
            for (int j = 0; ; j++) {
                const Job job = jobs[j];
                const int type = job.x & 7;
                if (type == JEND) break;
                if (type >= JR) continue;
                const int nb = (job.x >> 3) & 15, c0 = ((job.x >> 7) & 63) * 128, seg0 = (job.x >> 13) & 63, kb0 = (job.x >> 19) & 127,
                          nkb = job.y >> 16;
                const CUtensorMap *ta = &P.a[type], *tb = nb == 8 ? &P.b[type] : &P.c[type];
                const int nbox = nb == 8 ? 1 : nb;
                auto ready = [&]() {
                    bool ok = true;
                    if (type == JP) ok = (int)(ld_acquire(g_cnt + CNT_ATT + (seg0 >> 3)) - ep * 256) >= 0;
                    else for (int i = lane; i < nkb; i += 32) ok &= (int)(ld_acquire(g_prog + kb0 + i) - (ep * 128 + seg0 + nb)) >= 0;
                    return __all_sync(0xffffffffu, ok);
                };
                auto loadA = [&](int kb) {
                    const uint32_t full = bo + SB_FULL + 8 * sa;
                    mbar_wait_long(bo + SB_EMPTY + 8 * sa, pa);
                    expect_e(full, 16384 + nb * 4096);
                    tma2d_e(sb + sa * sz, ta, c0, (kb0 + kb) * 64, full);
                    tma2d_e(sb + sa * sz + 8192, ta, c0 + 64, (kb0 + kb) * 64, full);
                    if (++sa == ns) { sa = 0; pa ^= 1; }
                };
                auto loadB = [&](int kb) {
                    for (int i = 0; i < nbox; i++)
                        tma2d_e(sb + sl * sz + 16384 + i * 4096, tb, (kb0 + kb) * 64, (seg0 + i) * 32, bo + SB_FULL + 8 * sl);
                    if (++sl == ns) sl = 0;
                };
                int pre = 0;
                if (type >= JP) {
                    if (!ready()) {
                        pre = ns;
#pragma unroll 1
                        for (int kb = 0; kb < pre; kb++) loadA(kb);
                        for (int c = 0; c < SPIN_LIM && !ready(); c++) { }
                    }
                    if (lane == 0) TLS(96 + blockIdx.x, 53);
                    asm volatile("fence.proxy.async.global;" ::: "memory");
                    if (lane == 0) TLS(96 + blockIdx.x, 54);
                }
#pragma unroll 1
                for (int kb = 0; kb < nkb; kb++) { if (kb >= pre) loadA(kb); loadB(kb); }
                if (j == 0) ep = ld_epoch();
            }
            if (!EPC) {
                asm volatile("griddepcontrol.wait;" ::: "memory");
                if (blockIdx.x == 0 && lane == 0) g_epoch = ep;
            }
        } else if (warp == 9) {
            bar_sync(3, 96);
            if (lane == 0) {
                const uint32_t ep = ld_epoch();
                uint32_t n = 0;
                for (int j = 0; ; j++) {
                    const Job job = jobs[j];
                    const int type = job.x & 7;
                    if (type == JEND) break;
                    if (type == JS) continue;
                    const int nb = (job.x >> 3) & 15, ct = (job.x >> 7) & 63, seg0 = (job.x >> 13) & 63, ns = (job.y >> 4) & 15;
                    for (int wg = 0; wg < 2; wg++) {
                        const uint32_t src = sb + S_STG + wg * 32768;
                        mbar_wait_long(sb + SB_STAGED + 8 * wg, n & 1);
                        if (type == JV) bulk_st(g_vx + ((ct * 2 + wg) * 64 + seg0) * 256, src, nb * 4096);
                        else if (type == JR) {
                            for (int u = job.y & 15, i = 0; u < 2 * nb; u += ns, i++) tma_st(&P.sto, src + i * 2048, DM + ct * 128 + wg * 64, seg0 * 32 + u * 16);
                        } else if (ns > 1) bulk_st(part_ptr(job, wg) + (job.y & 15) * nb * 256, src, nb * 4096);
                        else tma_st(&P.st[type != JQ], src, (type == JO ? DM : 0) + ct * 128 + wg * 64, seg0 * 32);
                    }
                    asm volatile("cp.async.bulk.commit_group;" ::: "memory");
                    asm volatile("cp.async.bulk.wait_group.read 0;" ::: "memory");
                    mbar_arrive(sb + SB_FREE);
                    asm volatile("cp.async.bulk.wait_group 0;" ::: "memory");
                    if (type == JV) { st_release(g_flagv + ct * 128 + seg0, ep); g_flagv[ct * 128 + 64 + seg0] = ep; }
                    if (type == JQ) red_release(g_cnt + CNT_Q + (seg0 >> 3), 1);
                    if (type == JO && ns > 1) red_release(g_cnt + CNT_O + ((job.y >> 8) & 255) * 5 + ct, 1);
                    n++;
                }
            }
        } else {
            const uint32_t ep = __shfl_sync(0xffffffffu, ld_epoch(), 0);
            bar_arrive(3, 96);
            const float scl = 0.22360679774997896f * 1.4426950408889634f;
            for (int p = blockIdx.x * 2 + warp - 10; p < SEQ / 2; p += 2 * NSIDE) {
                const int t0 = 4 * (p >> 1) + (p & 1);
                wait_ge(g_cnt + CNT_Q + (max(t0 - 14, 0) >> 8), ep * 15);
                wait_ge(g_cnt + CNT_Q + (t0 >> 8), ep * 15);
                const bf16* base = g_qkvA + lane * 20;
                uint32_t w[18][10];
                auto row = [&](int j) { if (j < 18) ld20(base + (size_t)max(t0 + 2 - 2 * (j % 9), 0) * 1920 + (j < 9 ? 640 : 1280), w[j]); };
                float l0[8], l1[8];
                {
                    uint32_t u0[10], u1[10];
                    float q0[20], q1[20];
                    ld20(base + (size_t)t0 * 1920, u0); ld20(base + (size_t)(t0 + 2) * 1920, u1);
                    row(0); row(1);
#pragma unroll
                    for (int i = 0; i < 10; i++) { q0[2 * i] = bf_lo(u0[i]); q0[2 * i + 1] = bf_hi(u0[i]); q1[2 * i] = bf_lo(u1[i]); q1[2 * i + 1] = bf_hi(u1[i]); }
#pragma unroll
                    for (int j = 0; j < 9; j++) {
                        row(j + 2);
                        blk(warp);
                        float a0 = 0.f, a1 = 0.f;
#pragma unroll
                        for (int i = 0; i < 10; i++) {
                            const float lo = bf_lo(w[j][i]), hi = bf_hi(w[j][i]);
                            if (j > 0) a0 = fmaf(q0[2 * i + 1], hi, fmaf(q0[2 * i], lo, a0));
                            if (j < 8) a1 = fmaf(q1[2 * i + 1], hi, fmaf(q1[2 * i], lo, a1));
                        }
                        const bool in = t0 + 2 - 2 * j >= 0;
                        if (j > 0) l0[j - 1] = in ? a0 * scl : -3.0e38f;
                        if (j < 8) l1[j] = in ? a1 * scl : -3.0e38f;
                    }
                }
                float m0 = l0[0], m1 = l1[0], s0 = 0.f, s1 = 0.f;
#pragma unroll
                for (int j = 1; j < 8; j++) { m0 = fmaxf(m0, l0[j]); m1 = fmaxf(m1, l1[j]); }
#pragma unroll
                for (int j = 0; j < 8; j++) { l0[j] = ex2(l0[j] - m0); s0 += l0[j]; l1[j] = ex2(l1[j] - m1); s1 += l1[j]; }
                float o0[20], o1[20];
#pragma unroll
                for (int i = 0; i < 20; i++) o0[i] = o1[i] = 0.f;
#pragma unroll
                for (int j = 0; j < 9; j++) {
                    row(j + 11);
                    blk(warp);
#pragma unroll
                    for (int i = 0; i < 10; i++) {
                        const float lo = bf_lo(w[9 + j][i]), hi = bf_hi(w[9 + j][i]);
                        if (j > 0) { o0[2 * i] = fmaf(l0[j - 1], lo, o0[2 * i]); o0[2 * i + 1] = fmaf(l0[j - 1], hi, o0[2 * i + 1]); }
                        if (j < 8) { o1[2 * i] = fmaf(l1[j], lo, o1[2 * i]); o1[2 * i + 1] = fmaf(l1[j], hi, o1[2 * i + 1]); }
                    }
                }
                s0 = 1.f / s0; s1 = 1.f / s1;
                uint2* dst = reinterpret_cast<uint2*>(g_oA + (size_t)t0 * DM + lane * 20);
#pragma unroll
                for (int i = 0; i < 5; i++) {
                    dst[i] = make_uint2(pack2(o0[4 * i] * s0, o0[4 * i + 1] * s0), pack2(o0[4 * i + 2] * s0, o0[4 * i + 3] * s0));
                    dst[i + 2 * DM / 4] = make_uint2(pack2(o1[4 * i] * s1, o1[4 * i + 1] * s1), pack2(o1[4 * i + 2] * s1, o1[4 * i + 3] * s1));
                }
                __syncwarp();
                if (lane == 0) red_release(g_cnt + CNT_ATT + (t0 >> 8), 2);
                if (tid == 320) TLS(96 + blockIdx.x, 44 + p / 144);
            }
            const int wg = warp - 10;
            uint32_t m = 0;
            for (int j = 0; ; j++) {
                const Job job = jobs[j];
                if ((job.x & 7) == JEND) break;
                if ((job.x & 7) != JS) continue;
                const int nb = (job.x >> 3) & 15, ct = (job.x >> 7) & 63, ns = (job.y >> 4) & 15;
                wait_ge(g_cnt + CNT_O + ((job.y >> 8) & 255) * 5 + ct, ep * ns);
                for (int u = job.y & 15; u < 2 * nb; u += ns, m++) {
                    const uint32_t rs = sb + S_RST + wg * 4096 + (m & 1) * 2048;
                    if (lane == 0) asm volatile("cp.async.bulk.wait_group.read 1;" ::: "memory");
                    __syncwarp();
#pragma unroll 1
                    for (int h = 0; h < 4; h += 2) {
                        const uint4* part = part_ptr(job, wg) + u * 128 + h * 32 + lane;
                        uint4 q[2][NKS];
#pragma unroll
                        for (int k = 0; k < NKS; k++) {
                            q[0][k] = q[1][k] = make_uint4(0, 0, 0, 0);
                            if (k < ns) { q[0][k] = ld_pkt(part + k * nb * 256); q[1][k] = ld_pkt(part + k * nb * 256 + 32); }
                        }
#pragma unroll
                        for (int i = 0; i < 2; i++) {
                            float r[8] = {0, 0, 0, 0, 0, 0, 0, 0};
#pragma unroll
                            for (int k = 0; k < NKS; k++) {
                                r[0] += bf_lo(q[i][k].x); r[1] += bf_hi(q[i][k].x); r[2] += bf_lo(q[i][k].y); r[3] += bf_hi(q[i][k].y);
                                r[4] += bf_lo(q[i][k].z); r[5] += bf_hi(q[i][k].z); r[6] += bf_lo(q[i][k].w); r[7] += bf_hi(q[i][k].w);
                            }
                            stsm4t(rs + ((lane & 7) + ((lane >> 4) << 3)) * 128 + (((2 * (h + i) + ((lane >> 3) & 1)) ^ (lane & 7)) << 4),
                                   pack2(r[0], r[1]), pack2(r[2], r[3]), pack2(r[4], r[5]), pack2(r[6], r[7]));
                        }
                    }
                    asm volatile("fence.proxy.async.shared::cta;" ::: "memory");
                    __syncwarp();
                    if (lane == 0) {
                        tma_st(&P.sto, rs, DM + ct * 128 + wg * 64, ((job.x >> 13) & 63) * 32 + u * 16);
                        asm volatile("cp.async.bulk.commit_group;" ::: "memory");
                    }
                }
                if (tid == 320) TLS(96 + blockIdx.x, j);
            }
            if (lane == 0) asm volatile("cp.async.bulk.wait_group 0;" ::: "memory");
        }
    }
}

typedef CUresult (*EncodeFn)(CUtensorMap*, CUtensorMapDataType, cuuint32_t, void*, const cuuint64_t*, const cuuint64_t*,
                             const cuuint32_t*, const cuuint32_t*, CUtensorMapInterleave, CUtensorMapSwizzle,
                             CUtensorMapL2promotion, CUtensorMapFloatOOBfill);
static void make_map(EncodeFn enc, CUtensorMap* tm, const void* ptr, uint64_t cols, uint64_t rows, uint32_t bc, uint32_t br,
                     CUtensorMapSwizzle sw = CU_TENSOR_MAP_SWIZZLE_128B) {
    cuuint64_t dims[2] = {cols, rows}, strides[1] = {cols * 2};
    cuuint32_t box[2] = {bc, br}, es[2] = {1, 1};
    enc(tm, CU_TENSOR_MAP_DATA_TYPE_BFLOAT16, 2, const_cast<void*>(ptr), dims, strides, box, es, CU_TENSOR_MAP_INTERLEAVE_NONE, sw,
        CU_TENSOR_MAP_L2_PROMOTION_L2_128B, CU_TENSOR_MAP_FLOAT_OOB_FILL_NONE);
}

extern "C" void kernel_launch(void* const* d_in, const int* in_sizes, int n_in, void* d_out, int out_size) {
    (void)in_sizes; (void)n_in; (void)out_size;
    const bf16* A_x = (const bf16*)d_in[0];
    const bf16* A_wqkv = (const bf16*)d_in[1];
    const bf16* A_wo = (const bf16*)d_in[2];
    const bf16* B_x = (const bf16*)d_in[3];
    const bf16* B_mem0 = (const bf16*)d_in[4];
    const bf16* B_Wq = (const bf16*)d_in[5];
    const bf16* B_Wk = (const bf16*)d_in[6];
    const bf16* B_Wv = (const bf16*)d_in[7];
    const bf16* B_Wo = (const bf16*)d_in[8];
    bf16* out = (bf16*)d_out;

    static EncodeFn enc = nullptr;
    static void *p_ox, *p_qkv, *p_oA, *p_xch;
    if (!enc) {
        void* fn = nullptr; cudaDriverEntryPointQueryResult qr;
        cudaGetDriverEntryPoint("cuTensorMapEncodeTiled", &fn, cudaEnableDefault, &qr);
        enc = (EncodeFn)fn;
        cudaFuncSetAttribute(chain_kernel, cudaFuncAttributeMaxDynamicSharedMemorySize, CHAIN_SMEM);
        cudaFuncSetAttribute(side_kernel, cudaFuncAttributeMaxDynamicSharedMemorySize, SIDE_SMEM);
        cudaGetSymbolAddress(&p_ox, g_ox); cudaGetSymbolAddress(&p_qkv, g_qkvA); cudaGetSymbolAddress(&p_oA, g_oA);
        cudaGetSymbolAddress(&p_xch, g_xch);
    }
    CUtensorMap tmX, tmX7, tmWq, tmWk, tmWv, tmWo, tmWb;
    {
        cuuint64_t dims[3] = {64, SEQ, 10}, strides[2] = {DM * 2, 128};
        cuuint32_t box[3] = {64, 32, NX}, es[3] = {1, 1, 1};
        enc(&tmX7, CU_TENSOR_MAP_DATA_TYPE_BFLOAT16, 3, const_cast<bf16*>(B_x), dims, strides, box, es, CU_TENSOR_MAP_INTERLEAVE_NONE, CU_TENSOR_MAP_SWIZZLE_128B,
            CU_TENSOR_MAP_L2_PROMOTION_L2_128B, CU_TENSOR_MAP_FLOAT_OOB_FILL_NONE);
    }
    make_map(enc, &tmX, B_x, DM, SEQ, 64, 32);
    make_map(enc, &tmWq, B_Wq, HE, DM, 64, 128);
    make_map(enc, &tmWk, B_Wk, HE, DM, 64, 128);
    make_map(enc, &tmWv, B_Wv, HE, DM, 64, 128);
    make_map(enc, &tmWo, B_Wo, DM, HE, 64, 64);
    make_map(enc, &tmWb, B_Wo, DM, HE, 16, 64, CU_TENSOR_MAP_SWIZZLE_32B);
    SideParams sp;
    make_map(enc, &sp.a[JV], B_Wv, HE, DM, 64, 64);
    make_map(enc, &sp.a[JQ], A_wqkv, 3 * DM, DM, 64, 64);
    make_map(enc, &sp.a[JP], A_wo, DM, DM, 64, 64);
    sp.a[JO] = tmWo;
    const void* act[4] = {B_x, A_x, p_oA, p_ox};
    for (int i = 0; i < 4; i++) {
        make_map(enc, &sp.b[i], act[i], i == JO ? HE : DM, SEQ, 64, 256);
        make_map(enc, &sp.c[i], act[i], i == JO ? HE : DM, SEQ, 64, 32);
    }
    make_map(enc, &sp.st[0], p_qkv, 3 * DM, SEQ, 64, 256);
    make_map(enc, &sp.st[1], out, OUTW, SEQ, 64, 256);
    make_map(enc, &sp.sto, out, OUTW, SEQ, 64, 16);

    cudaStream_t st = cudaStreamPerThread;
    chain_kernel<<<96, 512, CHAIN_SMEM, st>>>(tmX, tmX7, tmWq, tmWk, tmWv, tmWo, tmWb, sp.c[JO], B_mem0, (const char*)B_x,
                                              (const char*)(((uintptr_t)p_xch + 0x1fffff) & ~(uintptr_t)0x1fffff), out);
    cudaLaunchConfig_t cfg = {};
    cfg.gridDim = dim3(NSIDE); cfg.blockDim = dim3(384); cfg.dynamicSmemBytes = SIDE_SMEM; cfg.stream = st;
    cudaLaunchAttribute at[1];
    at[0].id = cudaLaunchAttributeProgrammaticStreamSerialization; at[0].val.programmaticStreamSerializationAllowed = 1;
    cfg.attrs = at; cfg.numAttrs = 1;
    cudaLaunchKernelEx(&cfg, side_kernel, sp);
}

#ifdef TL
extern "C" void ev_read(void* dst) { cudaMemcpyFromSymbol(dst, g_ev, sizeof(g_ev)); cudaMemcpyFromSymbol((char*)dst + sizeof(g_ev), g_epoch, 4); }
extern "C" void tc_read(void* dst) { cudaMemcpyFromSymbol(dst, g_tc, sizeof(g_tc)); }
extern "C" void tl_read(void* dst, void* jobs) { cudaMemcpyFromSymbol(dst, g_tl, sizeof(g_tl)); cudaMemcpyFromSymbol(jobs, c_jobs, sizeof(c_jobs)); }
#endif
#ifdef DEV
extern "C" void dev_read(void* dst, int which) {
    if (which == 0) cudaMemcpyFromSymbol(dst, g_dbg, sizeof(g_dbg));
    if (which == 1) cudaMemcpyFromSymbol(dst, g_ox, sizeof(g_ox));
    if (which == 3) cudaMemcpyFromSymbol(dst, g_cal, sizeof(g_cal));
    if (which == 5) cudaMemcpyToSymbol(g_s0, dst, 4);
    if (which == 4) {
        void* p; cudaGetSymbolAddress(&p, g_pp); cudaMemset(p, 0, sizeof(g_pp));
        cudaFuncSetAttribute(calib_kernel, cudaFuncAttributeMaxDynamicSharedMemorySize, 200000);
        calib_kernel<<<132, 32, 200000>>>(); cudaDeviceSynchronize();
        cudaMemcpyFromSymbol(dst, g_off, sizeof(g_off));
    }
}
#endif
```
